```python
import torch

def _softmax(x, axis=-1):
    return torch.softmax(x, dim=axis)
def _gelu(x):
    return torch.nn.functional.gelu(x, approximate="tanh")
def _silu(x):
    return torch.nn.functional.silu(x)
def _sigmoid(x):
    return torch.sigmoid(x)
def _layernorm(x, axis=-1, eps=1e-5):
    m = x.mean(dim=axis, keepdim=True)
    v = x.var(dim=axis, keepdim=True, unbiased=False)
    return (x - m) / torch.sqrt(v + eps)
def _scatter_add(tgt, idx, src, axis=0):
    return tgt.clone().index_add_(axis, idx, src)
def _segment_sum(src, seg, n):
    out = torch.zeros((n,) + src.shape[1:], dtype=src.dtype)
    return out.index_add_(0, seg, src)
def _pad(x, pw):
    flat = tuple(v for pair in reversed(pw) for v in pair)
    return torch.nn.functional.pad(x, flat)

kernel_name = 'gated_mix__linear_kernel_hedgehog__grouped_kv_mqa__prompt'

def setup_inputs():

    _w = (lambda a: (lambda t: t.to(torch.bfloat16) if t.is_floating_point() else t)(torch.as_tensor(a)))
    def _A_setup():
        B, S, D, H = 1, 2048, 448, 16
        Dh = D // H
        return {
            "x": _w((lambda *s: torch.randn(*s, dtype=torch.bfloat16) * 0.05)(B, S, D)),
            "wqkv": _w((lambda *s: torch.randn(*s, dtype=torch.bfloat16) * 1.6)(D, 3 * D)),
            "w_phi": _w((lambda *s: torch.randn(*s, dtype=torch.bfloat16) * 1.6)(H, Dh, Dh) * (Dh ** -0.5)),
            "wo": _w((lambda *s: torch.randn(*s, dtype=torch.bfloat16) * 0.05)(D, D)),
        }
    _A_in = _A_setup()

    def _B_setup():
        B, S, D, H = 1, 2048, 448, 16
        Dh = D // H
        return {
            "x": _w((lambda *s: torch.randn(*s, dtype=torch.bfloat16) * 0.05)(B, S, D)),
            "wq": _w((lambda *s: torch.randn(*s, dtype=torch.bfloat16) * 1.6)(D, H * Dh)),
            "wk": _w((lambda *s: torch.randn(*s, dtype=torch.bfloat16) * 1.6)(D, Dh)),
            "wv": _w((lambda *s: torch.randn(*s, dtype=torch.bfloat16) * 0.05)(D, Dh)),
            "wo": _w((lambda *s: torch.randn(*s, dtype=torch.bfloat16) * 0.05)(H * Dh, D)),
        }
    _B_in = _B_setup()

    return {
        "A_x": _A_in["x"],
        "A_wqkv": _A_in["wqkv"],
        "A_w_phi": _A_in["w_phi"],
        "A_wo": _A_in["wo"],
        "B_x": _B_in["x"],
        "B_wq": _B_in["wq"],
        "B_wk": _B_in["wk"],
        "B_wv": _B_in["wv"],
        "B_wo": _B_in["wo"],
        "gate_w": _w((lambda *s: torch.randn(*s, dtype=torch.bfloat16) * 0.05)(448) * 16.0),
    }

def reference(A_x, A_wqkv, A_w_phi, A_wo, B_x, B_wq, B_wk, B_wv, B_wo, gate_w):
    def _A_ref(x, wqkv, w_phi, wo):
        B, S, D = x.shape
        H = 16; Dh = D // H
        qkv = (lambda x, *d: x.permute(*d))((x @ wqkv).reshape(B, S, 3, H, Dh), 2, 0, 3, 1, 4)
        q, k, v = qkv[0], qkv[1], qkv[2]
        pq = torch.einsum("bhsd,hdf->bhsf", q, w_phi)
        pk = torch.einsum("bhsd,hdf->bhsf", k, w_phi)
        phi_q = torch.concatenate([_softmax(pq, axis=-1), _softmax(-pq, axis=-1)], axis=-1)
        phi_k = torch.concatenate([_softmax(pk, axis=-1), _softmax(-pk, axis=-1)], axis=-1)
        kv = torch.einsum("bhsf,bhsd->bhfd", phi_k, v)
        z  = torch.einsum("bhsf->bhf", phi_k)
        num = torch.einsum("bhqf,bhfd->bhqd", phi_q, kv)
        den = torch.einsum("bhqf,bhf->bhq", phi_q, z)[..., None] + 1e-6
        o = num / den
        return (lambda x, *d: x.permute(*d))(o, 0, 2, 1, 3).reshape(B, S, D) @ wo

    def _B_ref(x, wq, wk, wv, wo):
        B, S, D = x.shape
        H = 16
        Dh = D // H
        q = (lambda x, *d: x.permute(*d))((x @ wq).reshape(B, S, H, Dh), 0, 2, 1, 3)
        k = x @ wk
        v = x @ wv
        scores = torch.einsum("bhqd,bkd->bhqk", q, k) * (Dh ** -0.5)
        p = _softmax(scores, axis=-1)
        o = torch.einsum("bhqk,bkd->bhqd", p, v)
        return (lambda x, *d: x.permute(*d))(o, 0, 2, 1, 3).reshape(B, S, H * Dh) @ wo

    x = A_x
    g = _sigmoid((x * gate_w).sum(-1, keepdims=True))
    a = _A_ref(x, A_wqkv, A_w_phi, A_wo)
    b = _B_ref(x, B_wq, B_wk, B_wv, B_wo)
    return g * a + (1 - g) * b
```

```cpp
#include <cuda_runtime.h>
#include <cuda_bf16.h>
#include <cuda.h>
#include <stdint.h>

namespace {

constexpr int SEQ = 2048, DM = 448;
constexpr uint32_t PMASK = 0xB6DAu;
constexpr int MID = 4;

constexpr uint32_t SM_STAGE = 49152;
constexpr uint32_t SM_RING = 0;
constexpr uint32_t SM_VEXT = 81920;
constexpr uint32_t SM_PHIK = 98304;
constexpr uint32_t SM_PHIQ = 131072;
constexpr uint32_t SM_KVX = 163840;
constexpr uint32_t SM_WPHI = 196608;
constexpr uint32_t SM_QEXT = 204800;
constexpr uint32_t SM_TO = 131072;
constexpr uint32_t SM_TW = 188416;
constexpr uint32_t SM_BAR = 225280;
constexpr uint32_t B_P1F = SM_BAR, B_P1E = SM_BAR + 32, B_RF = SM_BAR + 64, B_RE = SM_BAR + 128, B_TF = SM_BAR + 192,
                   B_TD = SM_BAR + 304, B_MID = SM_BAR + 360, SM_WMAX = SM_BAR + 384;
constexpr uint32_t SM_TOTAL = SM_BAR + 512 + 1024;

__device__ __align__(1024) uint8_t g_kv[16 * 16384];
__device__ __align__(16) float g_kn[4 * SEQ];
__device__ __align__(16) float g_gate[SEQ];
__device__ __align__(16) float g_kvsum[2][16 * 2048];
__device__ __align__(1024) __nv_bfloat16 g_ocat[SEQ * 896];
__device__ uint32_t g_cnt_kv[16 * 8], g_cnt_kva[8 * 8], g_cnt_oa[32 * 8], g_cnt_ob[32 * 8];
__device__ uint32_t g_vmax[2], g_epoch, g_done, g_abort;

__device__ __forceinline__ uint64_t make_desc(uint32_t saddr, uint32_t lbo, uint32_t sbo, uint32_t swz) {
    return (uint64_t)((saddr & 0x3FFFF) >> 4) | ((uint64_t)(lbo >> 4) << 16) | ((uint64_t)(sbo >> 4) << 32) | ((uint64_t)swz << 62);
}
#define WG_FENCE() asm volatile("wgmma.fence.sync.aligned;" ::: "memory")
#define WG_COMMIT() asm volatile("wgmma.commit_group.sync.aligned;" ::: "memory")
#define WG_WAIT(n) asm volatile("wgmma.wait_group.sync.aligned %0;" ::"n"(n) : "memory")
template <int N> __device__ __forceinline__ void fence_regs(float (&r)[N]) {
#pragma unroll
    for (int i = 0; i < N; i++) asm volatile("" : "+f"(r[i])::"memory");
}
template <int N> __device__ __forceinline__ void fence_regs(uint32_t (&r)[N][4]) {
#pragma unroll
    for (int i = 0; i < N; i++) asm volatile("" : "+r"(r[i][0]), "+r"(r[i][1]), "+r"(r[i][2]), "+r"(r[i][3])::"memory");
}
__device__ __forceinline__ void mbar_init(uint32_t bar, uint32_t cnt) { asm volatile("mbarrier.init.shared::cta.b64 [%0], %1;" ::"r"(bar), "r"(cnt) : "memory"); }
__device__ __forceinline__ void mbar_expect_tx(uint32_t bar, uint32_t bytes) { asm volatile("mbarrier.arrive.expect_tx.shared::cta.b64 _, [%0], %1;" ::"r"(bar), "r"(bytes) : "memory"); }
__device__ __forceinline__ void mbar_arrive(uint32_t bar) { asm volatile("mbarrier.arrive.shared::cta.b64 _, [%0];" ::"r"(bar) : "memory"); }
__device__ __forceinline__ bool mbar_try(uint32_t bar, uint32_t parity) {
    uint32_t ok;
    asm volatile("{.reg .pred p; mbarrier.try_wait.parity.shared::cta.b64 p, [%1], %2; selp.b32 %0, 1, 0, p;}" : "=r"(ok) : "r"(bar), "r"(parity) : "memory");
    return ok;
}
__device__ __noinline__ void mbar_wait_slow(uint32_t bar, uint32_t parity) {
    for (uint32_t it = 0; it < (1u << 20); it++) {
        if (mbar_try(bar, parity)) return;
        if ((it & 255) == 255 && *(volatile uint32_t*)&g_abort) return;
    }
    *(volatile uint32_t*)&g_abort = 1;
}
__device__ __forceinline__ void mbar_wait(uint32_t bar, uint32_t parity) {
    if (!mbar_try(bar, parity)) mbar_wait_slow(bar, parity);
}
__device__ __forceinline__ uint32_t ld_acquire(const uint32_t* p) { uint32_t v; asm volatile("ld.acquire.gpu.global.u32 %0, [%1];" : "=r"(v) : "l"(p) : "memory"); return v; }
__device__ __noinline__ void flag_wait(const uint32_t* p, uint32_t target) {
    for (uint32_t it = 0; it < (1u << 21); it++) {
        if ((int32_t)(ld_acquire(p) - target) >= 0) return;
        if ((it & 255) == 255 && *(volatile uint32_t*)&g_abort) return;
    }
    *(volatile uint32_t*)&g_abort = 1;
}
__device__ __forceinline__ void flag_signal(uint32_t* p) {
    asm volatile("fence.proxy.async.global;\n\tfence.acq_rel.gpu;\n\tred.relaxed.gpu.global.add.u32 [%0], 1;" ::"l"(p) : "memory");
}
__device__ __forceinline__ void fence_async_smem() { asm volatile("fence.proxy.async.shared::cta;" ::: "memory"); }
__device__ __forceinline__ void fence_async_global() { asm volatile("fence.proxy.async.global;" ::: "memory"); }
__device__ __forceinline__ void bar_sync(int id, int n) { asm volatile("bar.sync %0, %1;" ::"r"(id), "r"(n) : "memory"); }
__device__ __forceinline__ void bulk_g2s(uint32_t dst, const void* src, uint32_t bytes, uint32_t bar) {
    asm volatile("cp.async.bulk.shared::cluster.global.mbarrier::complete_tx::bytes [%0], [%1], %2, [%3];" ::"r"(dst), "l"(src), "r"(bytes), "r"(bar) : "memory");
}
__device__ __forceinline__ void tma2d(uint32_t dst, const CUtensorMap* tm, int c0, int c1, uint32_t bar) {
    asm volatile("cp.async.bulk.tensor.2d.shared::cluster.global.mbarrier::complete_tx::bytes [%0], [%1, {%3, %4}], [%2];" ::"r"(dst), "l"(tm), "r"(bar), "r"(c0), "r"(c1) : "memory");
}
__device__ __forceinline__ void sts32(uint32_t a, uint32_t v) { asm volatile("st.shared.b32 [%0], %1;" ::"r"(a), "r"(v) : "memory"); }
__device__ __forceinline__ void sts64(uint32_t a, uint32_t v0, uint32_t v1) { asm volatile("st.shared.v2.b32 [%0], {%1,%2};" ::"r"(a), "r"(v0), "r"(v1) : "memory"); }
__device__ __forceinline__ void sts128(uint32_t a, uint32_t v0, uint32_t v1, uint32_t v2, uint32_t v3) { asm volatile("st.shared.v4.b32 [%0], {%1,%2,%3,%4};" ::"r"(a), "r"(v0), "r"(v1), "r"(v2), "r"(v3) : "memory"); }
__device__ __forceinline__ uint32_t lds32(uint32_t a) { uint32_t v; asm volatile("ld.shared.b32 %0, [%1];" : "=r"(v) : "r"(a) : "memory"); return v; }
__device__ __forceinline__ float ex2(float x) { float r; asm("ex2.approx.ftz.f32 %0, %1;" : "=f"(r) : "f"(x)); return r; }
__device__ __forceinline__ float rcp(float x) { float r; asm("rcp.approx.ftz.f32 %0, %1;" : "=f"(r) : "f"(x)); return r; }
__device__ __forceinline__ uint32_t pack_bf16(float lo, float hi) { uint32_t r; asm("cvt.rn.bf16x2.f32 %0, %1, %2;" : "=r"(r) : "f"(hi), "f"(lo)); return r; }
__device__ __forceinline__ float bf_lo(uint32_t v) { return __uint_as_float(v << 16); }
__device__ __forceinline__ float bf_hi(uint32_t v) { return __uint_as_float(v & 0xFFFF0000u); }
__device__ __forceinline__ uint32_t hfma(uint32_t a, uint32_t b, uint32_t c) { uint32_t r; asm("fma.rn.bf16x2 %0, %1, %2, %3;" : "=r"(r) : "r"(a), "r"(b), "r"(c)); return r; }

__device__ __forceinline__ void wg_ss_n120_ta0_tb1(float (&d)[60], uint64_t ad, uint64_t bd, int sc) {
    asm volatile("{.reg .pred p; setp.ne.b32 p, %62, 0;\n"
        "wgmma.mma_async.sync.aligned.m64n120k16.f32.bf16.bf16 {%0,%1,%2,%3,%4,%5,%6,%7,%8,%9,%10,%11,%12,%13,%14,%15,%16,%17,%18,%19,%20,%21,%22,%23,%24,%25,%26,%27,%28,%29,%30,%31,%32,%33,%34,%35,%36,%37,%38,%39,%40,%41,%42,%43,%44,%45,%46,%47,%48,%49,%50,%51,%52,%53,%54,%55,%56,%57,%58,%59}, %60, %61, p, 1, 1, 0, 1;}"
        : "+f"(d[0]),"+f"(d[1]),"+f"(d[2]),"+f"(d[3]),"+f"(d[4]),"+f"(d[5]),"+f"(d[6]),"+f"(d[7]),
          "+f"(d[8]),"+f"(d[9]),"+f"(d[10]),"+f"(d[11]),"+f"(d[12]),"+f"(d[13]),"+f"(d[14]),"+f"(d[15]),
          "+f"(d[16]),"+f"(d[17]),"+f"(d[18]),"+f"(d[19]),"+f"(d[20]),"+f"(d[21]),"+f"(d[22]),"+f"(d[23]),
          "+f"(d[24]),"+f"(d[25]),"+f"(d[26]),"+f"(d[27]),"+f"(d[28]),"+f"(d[29]),"+f"(d[30]),"+f"(d[31]),
          "+f"(d[32]),"+f"(d[33]),"+f"(d[34]),"+f"(d[35]),"+f"(d[36]),"+f"(d[37]),"+f"(d[38]),"+f"(d[39]),
          "+f"(d[40]),"+f"(d[41]),"+f"(d[42]),"+f"(d[43]),"+f"(d[44]),"+f"(d[45]),"+f"(d[46]),"+f"(d[47]),
          "+f"(d[48]),"+f"(d[49]),"+f"(d[50]),"+f"(d[51]),"+f"(d[52]),"+f"(d[53]),"+f"(d[54]),"+f"(d[55]),
          "+f"(d[56]),"+f"(d[57]),"+f"(d[58]),"+f"(d[59])
        : "l"(ad), "l"(bd), "r"(sc));
}
__device__ __forceinline__ void wg_rs_n56_tb1(float (&d)[28], const uint32_t (&a)[4], uint64_t bd, int sc) {
    asm volatile("{.reg .pred p; setp.ne.b32 p, %33, 0;\n"
        "wgmma.mma_async.sync.aligned.m64n56k16.f32.bf16.bf16 {%0,%1,%2,%3,%4,%5,%6,%7,%8,%9,%10,%11,%12,%13,%14,%15,%16,%17,%18,%19,%20,%21,%22,%23,%24,%25,%26,%27}, {%28,%29,%30,%31}, %32, p, 1, 1, 1;}"
        : "+f"(d[0]),"+f"(d[1]),"+f"(d[2]),"+f"(d[3]),"+f"(d[4]),"+f"(d[5]),"+f"(d[6]),"+f"(d[7]),
          "+f"(d[8]),"+f"(d[9]),"+f"(d[10]),"+f"(d[11]),"+f"(d[12]),"+f"(d[13]),"+f"(d[14]),"+f"(d[15]),
          "+f"(d[16]),"+f"(d[17]),"+f"(d[18]),"+f"(d[19]),"+f"(d[20]),"+f"(d[21]),"+f"(d[22]),"+f"(d[23]),
          "+f"(d[24]),"+f"(d[25]),"+f"(d[26]),"+f"(d[27])
        : "r"(a[0]),"r"(a[1]),"r"(a[2]),"r"(a[3]), "l"(bd), "r"(sc));
}
__device__ __forceinline__ void wg_ss_n32_ta1_tb1(float (&d)[16], uint64_t ad, uint64_t bd, int sc) {
    asm volatile("{.reg .pred p; setp.ne.b32 p, %18, 0;\n"
        "wgmma.mma_async.sync.aligned.m64n32k16.f32.bf16.bf16 {%0,%1,%2,%3,%4,%5,%6,%7,%8,%9,%10,%11,%12,%13,%14,%15}, %16, %17, p, 1, 1, 1, 1;}"
        : "+f"(d[0]),"+f"(d[1]),"+f"(d[2]),"+f"(d[3]),"+f"(d[4]),"+f"(d[5]),"+f"(d[6]),"+f"(d[7]),
          "+f"(d[8]),"+f"(d[9]),"+f"(d[10]),"+f"(d[11]),"+f"(d[12]),"+f"(d[13]),"+f"(d[14]),"+f"(d[15])
        : "l"(ad), "l"(bd), "r"(sc));
}
__device__ __forceinline__ void wg_ss_n32_ta0_tb1(float (&d)[16], uint64_t ad, uint64_t bd, int sc) {
    asm volatile("{.reg .pred p; setp.ne.b32 p, %18, 0;\n"
        "wgmma.mma_async.sync.aligned.m64n32k16.f32.bf16.bf16 {%0,%1,%2,%3,%4,%5,%6,%7,%8,%9,%10,%11,%12,%13,%14,%15}, %16, %17, p, 1, 1, 0, 1;}"
        : "+f"(d[0]),"+f"(d[1]),"+f"(d[2]),"+f"(d[3]),"+f"(d[4]),"+f"(d[5]),"+f"(d[6]),"+f"(d[7]),
          "+f"(d[8]),"+f"(d[9]),"+f"(d[10]),"+f"(d[11]),"+f"(d[12]),"+f"(d[13]),"+f"(d[14]),"+f"(d[15])
        : "l"(ad), "l"(bd), "r"(sc));
}
__device__ __forceinline__ void wg_rs_n128_tb0(float (&d)[64], const uint32_t (&a)[4], uint64_t bd, int sc) {
    asm volatile("{.reg .pred p; setp.ne.b32 p, %69, 0;\n"
        "wgmma.mma_async.sync.aligned.m64n128k16.f32.bf16.bf16 {%0,%1,%2,%3,%4,%5,%6,%7,%8,%9,%10,%11,%12,%13,%14,%15,%16,%17,%18,%19,%20,%21,%22,%23,%24,%25,%26,%27,%28,%29,%30,%31,%32,%33,%34,%35,%36,%37,%38,%39,%40,%41,%42,%43,%44,%45,%46,%47,%48,%49,%50,%51,%52,%53,%54,%55,%56,%57,%58,%59,%60,%61,%62,%63}, {%64,%65,%66,%67}, %68, p, 1, 1, 0;}"
        : "+f"(d[0]),"+f"(d[1]),"+f"(d[2]),"+f"(d[3]),"+f"(d[4]),"+f"(d[5]),"+f"(d[6]),"+f"(d[7]),
          "+f"(d[8]),"+f"(d[9]),"+f"(d[10]),"+f"(d[11]),"+f"(d[12]),"+f"(d[13]),"+f"(d[14]),"+f"(d[15]),
          "+f"(d[16]),"+f"(d[17]),"+f"(d[18]),"+f"(d[19]),"+f"(d[20]),"+f"(d[21]),"+f"(d[22]),"+f"(d[23]),
          "+f"(d[24]),"+f"(d[25]),"+f"(d[26]),"+f"(d[27]),"+f"(d[28]),"+f"(d[29]),"+f"(d[30]),"+f"(d[31]),
          "+f"(d[32]),"+f"(d[33]),"+f"(d[34]),"+f"(d[35]),"+f"(d[36]),"+f"(d[37]),"+f"(d[38]),"+f"(d[39]),
          "+f"(d[40]),"+f"(d[41]),"+f"(d[42]),"+f"(d[43]),"+f"(d[44]),"+f"(d[45]),"+f"(d[46]),"+f"(d[47]),
          "+f"(d[48]),"+f"(d[49]),"+f"(d[50]),"+f"(d[51]),"+f"(d[52]),"+f"(d[53]),"+f"(d[54]),"+f"(d[55]),
          "+f"(d[56]),"+f"(d[57]),"+f"(d[58]),"+f"(d[59]),"+f"(d[60]),"+f"(d[61]),"+f"(d[62]),"+f"(d[63])
        : "r"(a[0]),"r"(a[1]),"r"(a[2]),"r"(a[3]), "l"(bd), "r"(sc));
}
__device__ __forceinline__ void wg_rs_n32_tb1(float (&d)[16], const uint32_t (&a)[4], uint64_t bd, int sc) {
    asm volatile("{.reg .pred p; setp.ne.b32 p, %21, 0;\n"
        "wgmma.mma_async.sync.aligned.m64n32k16.f32.bf16.bf16 {%0,%1,%2,%3,%4,%5,%6,%7,%8,%9,%10,%11,%12,%13,%14,%15}, {%16,%17,%18,%19}, %20, p, 1, 1, 1;}"
        : "+f"(d[0]),"+f"(d[1]),"+f"(d[2]),"+f"(d[3]),"+f"(d[4]),"+f"(d[5]),"+f"(d[6]),"+f"(d[7]),
          "+f"(d[8]),"+f"(d[9]),"+f"(d[10]),"+f"(d[11]),"+f"(d[12]),"+f"(d[13]),"+f"(d[14]),"+f"(d[15])
        : "r"(a[0]),"r"(a[1]),"r"(a[2]),"r"(a[3]), "l"(bd), "r"(sc));
}
__device__ __forceinline__ void wg_ss_n112_ta0_tb1(float (&d)[56], uint64_t ad, uint64_t bd, int sc) {
    asm volatile("{.reg .pred p; setp.ne.b32 p, %58, 0;\n"
        "wgmma.mma_async.sync.aligned.m64n112k16.f32.bf16.bf16 {%0,%1,%2,%3,%4,%5,%6,%7,%8,%9,%10,%11,%12,%13,%14,%15,%16,%17,%18,%19,%20,%21,%22,%23,%24,%25,%26,%27,%28,%29,%30,%31,%32,%33,%34,%35,%36,%37,%38,%39,%40,%41,%42,%43,%44,%45,%46,%47,%48,%49,%50,%51,%52,%53,%54,%55}, %56, %57, p, 1, 1, 0, 1;}"
        : "+f"(d[0]),"+f"(d[1]),"+f"(d[2]),"+f"(d[3]),"+f"(d[4]),"+f"(d[5]),"+f"(d[6]),"+f"(d[7]),
          "+f"(d[8]),"+f"(d[9]),"+f"(d[10]),"+f"(d[11]),"+f"(d[12]),"+f"(d[13]),"+f"(d[14]),"+f"(d[15]),
          "+f"(d[16]),"+f"(d[17]),"+f"(d[18]),"+f"(d[19]),"+f"(d[20]),"+f"(d[21]),"+f"(d[22]),"+f"(d[23]),
          "+f"(d[24]),"+f"(d[25]),"+f"(d[26]),"+f"(d[27]),"+f"(d[28]),"+f"(d[29]),"+f"(d[30]),"+f"(d[31]),
          "+f"(d[32]),"+f"(d[33]),"+f"(d[34]),"+f"(d[35]),"+f"(d[36]),"+f"(d[37]),"+f"(d[38]),"+f"(d[39]),
          "+f"(d[40]),"+f"(d[41]),"+f"(d[42]),"+f"(d[43]),"+f"(d[44]),"+f"(d[45]),"+f"(d[46]),"+f"(d[47]),
          "+f"(d[48]),"+f"(d[49]),"+f"(d[50]),"+f"(d[51]),"+f"(d[52]),"+f"(d[53]),"+f"(d[54]),"+f"(d[55])
        : "l"(ad), "l"(bd), "r"(sc));
}


__device__ __forceinline__ uint32_t exp2_pair_fma(float y0, float y1, uint32_t one) {
    uint32_t e = __byte_perm(__float_as_uint(y0), __float_as_uint(y1), 0x6521);
    uint32_t m;
    asm("lop3.b32 %0, %1, 0x007F007F, %2, 0xEA;" : "=r"(m) : "r"(e), "r"(one));
    uint32_t t = hfma(m, 0x3EAC3EACu, 0xBC66BC66u);
    t = hfma(t, m, 0x3F2E3F2Eu);
    return e + t - m;
}

__device__ __forceinline__ void feature_map(float (&p)[28], uint32_t base0, uint32_t base1, int r, int c) {
    const float L2E = 1.4426950408889634f;
    const bool lo = c < 2;
#pragma unroll
    for (int rr = 0; rr < 2; rr++) {
        const int row = r + rr * 8;
        float x[14];
#pragma unroll
        for (int t = 0; t < 7; t++) { x[2 * t] = p[4 * t + 2 * rr] * L2E; x[2 * t + 1] = p[4 * t + 2 * rr + 1] * L2E; }
        float mx0 = fmaxf(fmaxf(fmaxf(x[0], x[1]), fmaxf(x[2], x[3])), fmaxf(x[4], x[5]));
        float mn0 = fminf(fminf(fminf(x[0], x[1]), fminf(x[2], x[3])), fminf(x[4], x[5]));
        float mx1 = fmaxf(fmaxf(fmaxf(x[8], x[9]), fmaxf(x[10], x[11])), fmaxf(x[12], x[13]));
        float mn1 = fminf(fminf(fminf(x[8], x[9]), fminf(x[10], x[11])), fminf(x[12], x[13]));
        const float mx3 = fmaxf(x[6], x[7]), mn3 = fminf(x[6], x[7]);
        if (lo) { mx0 = fmaxf(mx0, mx3); mn0 = fminf(mn0, mn3); } else { mx1 = fmaxf(mx1, mx3); mn1 = fminf(mn1, mn3); }
#pragma unroll
        for (int o = 1; o <= 2; o <<= 1) {
            mx0 = fmaxf(mx0, __shfl_xor_sync(0xffffffffu, mx0, o)); mn0 = fminf(mn0, __shfl_xor_sync(0xffffffffu, mn0, o));
            mx1 = fmaxf(mx1, __shfl_xor_sync(0xffffffffu, mx1, o)); mn1 = fminf(mn1, __shfl_xor_sync(0xffffffffu, mn1, o));
        }
        float ep[14], en[14];
        const float mxm = lo ? mx0 : mx1, mnm = lo ? mn0 : mn1;
#pragma unroll
        for (int i = 0; i < 14; i++) {
            const float mx = i < 6 ? mx0 : (i < 8 ? mxm : mx1), mn = i < 6 ? mn0 : (i < 8 ? mnm : mn1);
            ep[i] = ex2(x[i] - mx); en[i] = ex2(mn - x[i]);
        }
        float sp0 = ep[0] + ep[1] + ep[2] + ep[3] + ep[4] + ep[5], sn0 = en[0] + en[1] + en[2] + en[3] + en[4] + en[5];
        float sp1 = ep[8] + ep[9] + ep[10] + ep[11] + ep[12] + ep[13], sn1 = en[8] + en[9] + en[10] + en[11] + en[12] + en[13];
        const float sp3 = ep[6] + ep[7], sn3 = en[6] + en[7];
        if (lo) { sp0 += sp3; sn0 += sn3; } else { sp1 += sp3; sn1 += sn3; }
#pragma unroll
        for (int o = 1; o <= 2; o <<= 1) {
            sp0 += __shfl_xor_sync(0xffffffffu, sp0, o); sn0 += __shfl_xor_sync(0xffffffffu, sn0, o);
            sp1 += __shfl_xor_sync(0xffffffffu, sp1, o); sn1 += __shfl_xor_sync(0xffffffffu, sn1, o);
        }
        sp0 = rcp(sp0); sn0 = rcp(sn0); sp1 = rcp(sp1); sn1 = rcp(sn1);
        const float spm = lo ? sp0 : sp1, snm = lo ? sn0 : sn1;
        const uint32_t rb0 = base0 + row * 128, rb1 = base1 + row * 128, sw = row & 7;
#pragma unroll
        for (int t = 0; t < 7; t++) {
            const float a = t < 3 ? sp0 : (t == 3 ? spm : sp1), b = t < 3 ? sn0 : (t == 3 ? snm : sn1);
            const bool h1 = t > 3 || (t == 3 && !lo);
            const int fi = 8 * t + 2 * c - (h1 ? 28 : 0), fn = fi + 28;
            const uint32_t rb = h1 ? rb1 : rb0;
            sts32(rb + ((((uint32_t)fi >> 3) ^ sw) << 4) + (fi & 7) * 2, pack_bf16(ep[2 * t] * a, ep[2 * t + 1] * a));
            sts32(rb + ((((uint32_t)fn >> 3) ^ sw) << 4) + (fn & 7) * 2, pack_bf16(en[2 * t] * b, en[2 * t + 1] * b));
        }
    }
    {
        const int row = r + (c >> 1) * 8;
        sts128(((c & 1) ? base1 : base0) + row * 128 + ((7u ^ (row & 7)) << 4), 0, 0, 0, 0);
    }
}

__device__ __forceinline__ void phi_project(float (&acc)[60], float (&p)[28], uint32_t sb) {
    uint32_t a[4][4];
#pragma unroll
    for (int kk = 0; kk < 4; kk++) {
        a[kk][0] = pack_bf16(acc[8 * kk], acc[8 * kk + 1]);
        a[kk][1] = pack_bf16(acc[8 * kk + 2], acc[8 * kk + 3]);
        a[kk][2] = kk < 3 ? pack_bf16(acc[8 * kk + 4], acc[8 * kk + 5]) : 0u;
        a[kk][3] = kk < 3 ? pack_bf16(acc[8 * kk + 6], acc[8 * kk + 7]) : 0u;
    }
#pragma unroll
    for (int i = 0; i < 28; i++) p[i] = 0.f;
    fence_regs(p); fence_regs(a);
    const uint64_t db = make_desc(sb + SM_WPHI, 8192, 1024, 1);
    WG_FENCE();
#pragma unroll
    for (int kk = 0; kk < 4; kk++) wg_rs_n56_tb1(p, a[kk], db + kk * 128, kk);
    WG_COMMIT();
    WG_WAIT(0);
    fence_regs(p);
}

__global__ void __launch_bounds__(512, 1)
fused_kernel(const __grid_constant__ CUtensorMap tmX, const __grid_constant__ CUtensorMap tmWqkv, const __grid_constant__ CUtensorMap tmWq,
             const __grid_constant__ CUtensorMap tmWoA, const __grid_constant__ CUtensorMap tmWoB, const __grid_constant__ CUtensorMap tmO,
             const __nv_bfloat16* __restrict__ w_phi, const __nv_bfloat16* __restrict__ wk, const __nv_bfloat16* __restrict__ wv,
             const __nv_bfloat16* __restrict__ gate_w, __nv_bfloat16* __restrict__ out) {
    extern __shared__ uint8_t smem_raw[];
    const uint32_t sb = ((uint32_t)__cvta_generic_to_shared(smem_raw) + 1023) & ~1023u;
    const int tid = threadIdx.x, lane = tid & 31;
    const int warp = __shfl_sync(0xffffffffu, tid >> 5, 0);
    const int wg = warp >> 2, wq = warp & 3, th = wg >> 1, sp = wg & 1;
    const int tb = blockIdx.x >> 3, hp = blockIdx.x & 7;
    const int r = wq * 16 + (lane >> 2), c = lane & 3;

    auto p1_load = [&](int kb) {
        const uint32_t st = sb + (kb & 3) * SM_STAGE, bar = sb + B_P1F + 8 * (kb & 3);
        mbar_expect_tx(bar, 16384 + 4 * 7168);
        tma2d(st, &tmX, kb * 64, tb * 128, bar);
        tma2d(st + 16384 + 2 * 8192, &tmWqkv, hp * 56, kb * 64, bar);
        tma2d(st + 16384 + 3 * 8192, &tmWq, hp * 56, kb * 64, bar);
        tma2d(st + 16384, &tmWqkv, 448 + hp * 56, kb * 64, bar);
        tma2d(st + 16384 + 8192, &tmWqkv, 896 + hp * 56, kb * 64, bar);
    };
    if (tid == 0) {
        for (int i = 0; i < 4; i++) { mbar_init(sb + B_P1F + 8 * i, 2); mbar_init(sb + B_P1E + 8 * i, 16); }
        for (int i = 0; i < 8; i++) { mbar_init(sb + B_RF + 8 * i, 1); mbar_init(sb + B_RE + 8 * i, 16); }
        for (int i = 0; i < 14; i++) mbar_init(sb + B_TF + 8 * i, 2);
        for (int i = 0; i < 7; i++) mbar_init(sb + B_TD + 8 * i, 4);
        mbar_init(sb + B_MID, 16);
        asm volatile("fence.mbarrier_init.release.cluster;" ::: "memory");
        fence_async_smem();
        for (int kb = 0; kb < 4; kb++) p1_load(kb);
    }
    const uint32_t epoch = *(volatile uint32_t*)&g_epoch, par = epoch & 1;

    uint2 sl[2][2];
    if (warp < 7) {
#pragma unroll
        for (int i = 0; i < 2; i++) {
            const int k = warp * 64 + lane + 32 * i;
#pragma unroll
            for (int hh = 0; hh < 2; hh++) {
                const int q4 = 2 * hp + hh;
                uint2 v = make_uint2(0u, 0u);
                if (q4 < 7) v = __ldg((const uint2*)(wk + k * 28 + 4 * q4));
                else if (q4 < 14) v = __ldg((const uint2*)(wv + k * 28 + 4 * (q4 - 7)));
                else if (q4 == 14) v.x = __ldg((const unsigned short*)gate_w + k);
                sl[i][hh] = v;
            }
        }
    }
    auto slice_store = [&](int kb) {
#pragma unroll
        for (int i = 0; i < 2; i++) {
            const int row = lane + 32 * i;
            sts128(sb + (kb & 3) * SM_STAGE + 16384 + 2 * 8192 + row * 128 + ((7u ^ (row & 7)) << 4), sl[i][0].x, sl[i][0].y, sl[i][1].x, sl[i][1].y);
        }
        fence_async_smem();
        __syncwarp();
        if (lane == 0) mbar_arrive(sb + B_P1F + 8 * (kb & 3));
    };
    {
        uint32_t wv4[4];
#pragma unroll
        for (int i = 0; i < 4; i++) {
            const int w = tid + 512 * i, k = w >> 5, n = (w & 31) * 2;
            const int hk = k >= 28, hn = n >= 28;
            wv4[i] = (k < 56 && n < 56 && hk == hn) ? __ldg((const uint32_t*)(w_phi + (2 * hp + hk) * 784 + (k - 28 * hk) * 28 + (n - 28 * hn))) : 0u;
        }
        if (tid < 64) *(float4*)&g_kvsum[par ^ 1][blockIdx.x * 256 + tid * 4] = make_float4(0.f, 0.f, 0.f, 0.f);
        if (tid == 64 && blockIdx.x == 0) g_vmax[par ^ 1] = 0u;
        __syncthreads();
        if (warp < 4) slice_store(warp);
#pragma unroll
        for (int i = 0; i < 4; i++) {
            const int w = tid + 512 * i, k = w >> 5, n = (w & 31) * 2;
            sts32(sb + SM_WPHI + k * 128 + ((((uint32_t)n >> 3) ^ (k & 7)) << 4) + (n & 7) * 2, wv4[i]);
        }
        fence_async_smem();
    }

    {
        float acc[60];
#pragma unroll
        for (int i = 0; i < 60; i++) acc[i] = 0.f;
        fence_regs(acc);
        const uint64_t da0 = make_desc(sb + th * 8192, 16, 1024, 1);
        const uint64_t db0 = make_desc(sb + 16384 + sp * 16384, 8192, 1024, 1);
#pragma unroll
        for (int kb = 0; kb < 7; kb++) {
            mbar_wait(sb + B_P1F + 8 * (kb & 3), kb >> 2);
            WG_FENCE();
#pragma unroll
            for (int kk = 0; kk < 4; kk++)
                wg_ss_n120_ta0_tb1(acc, da0 + (uint64_t)((kb & 3) * (SM_STAGE >> 4) + kk * 2), db0 + (uint64_t)((kb & 3) * (SM_STAGE >> 4) + kk * 128), (kb | kk) != 0);
            WG_COMMIT();
            if (kb >= 1 && kb <= 3) {
                WG_WAIT(1);
                if (lane == 0) mbar_arrive(sb + B_P1E + 8 * (kb - 1));
                if (warp == kb + 3) {
                    mbar_wait(sb + B_P1E + 8 * (kb - 1), 0);
                    if (lane == 0) p1_load(kb + 3);
                    slice_store(kb + 3);
                }
            }
        }
        WG_WAIT(0);
        fence_regs(acc);
        __syncthreads();

        const int tok0 = tb * 128 + th * 64;
        if (sp == 1) {
            const int j = 8 * hp + 2 * c;
#pragma unroll
            for (int rr = 0; rr < 2; rr++) {
                const int key = tok0 + r + 8 * rr, kr = key & 127;
                const bool poly = (PMASK >> ((kr >> 3) & 15)) & 1;
                uint8_t* kvb = g_kv + tb * 16384 + kr * 64;
                const uint32_t sw = (kr >> 1) & 3;
                const float v0 = acc[28 + 2 * rr], v1 = acc[29 + 2 * rr];
                const uint32_t pk = pack_bf16(v0, v1);
                const float f0 = bf_lo(pk), f1 = bf_hi(pk);
                float kn = 0.f, vm = 0.f;
                if (j < 28) {
                    *(uint32_t*)(kvb + ((((uint32_t)j >> 3) ^ sw) << 4) + (j & 7) * 2) = poly ? pack_bf16(2.f * f0, 2.f * f1) : pk;
                    kn = f0 * f0 + f1 * f1;
                } else if (j < 56) {
                    const int d = j - 28;
                    *(uint32_t*)(kvb + 8192 + ((((uint32_t)d >> 3) ^ sw) << 4) + (d & 7) * 2) = pk;
                    vm = fmaxf(fabsf(f0), fabsf(f1));
                    if (!(vm <= 3.0e38f)) vm = 3.0e38f;
                } else if (c == 0) {
                    g_gate[key] = 1.f / (1.f + __expf(-v0));
                } else if (c == 1) {
                    *(uint2*)(kvb + ((3u ^ sw) << 4) + 8) = poly ? make_uint2(0x44404000u, 0x0000BFFFu) : make_uint2(0x00003F80u, 0u);
                } else if (c == 2) {
                    *(uint2*)(kvb + 8192 + ((3u ^ sw) << 4) + 8) = make_uint2(0x00003F80u, 0u);
                }
                if (hp < 4) {
                    kn += __shfl_xor_sync(0xffffffffu, kn, 1); kn += __shfl_xor_sync(0xffffffffu, kn, 2);
                    if (c == 0) g_kn[hp * SEQ + key] = kn;
                }
                if (hp >= 3 && hp < 7) {
                    const uint32_t vmu = __reduce_max_sync(0xffffffffu, __float_as_uint(vm));
                    if (lane == 0) atomicMax(&g_vmax[par], vmu);
                }
            }
            bar_sync(1 + wg, 128);
            if ((tid & 127) == 0) flag_signal(&g_cnt_kv[tb * 8]);
            const float qs = 0.18898223650461362f * 1.4426950408889634f;
#pragma unroll
            for (int t = 0; t < 7; t++) {
                const bool h1 = t > 3 || (t == 3 && c >= 2);
                const uint32_t a = sb + SM_QEXT + (th * 2 + (h1 ? 1 : 0)) * 5120 + r * 80 + (8 * t + 2 * c - (h1 ? 28 : 0)) * 2;
                sts32(a, pack_bf16(acc[32 + 4 * t] * qs, acc[33 + 4 * t] * qs));
                sts32(a + 640, pack_bf16(acc[34 + 4 * t] * qs, acc[35 + 4 * t] * qs));
            }
            float p[28];
            phi_project(acc, p, sb);
            feature_map(p, sb + SM_PHIQ + th * 8192, sb + SM_PHIQ + (2 + th) * 8192, r, c);
            fence_async_smem();
        } else {
#pragma unroll
            for (int t = 0; t < 7; t++) {
                const bool h1 = t > 3 || (t == 3 && c >= 2);
                const int d = 8 * t + 2 * c - (h1 ? 28 : 0);
#pragma unroll
                for (int rr = 0; rr < 2; rr++) {
                    const int row = th * 64 + r + 8 * rr;
                    sts32(sb + SM_VEXT + (h1 ? 8192 : 0) + row * 64 + ((((uint32_t)d >> 3) ^ ((row >> 1) & 3)) << 4) + (d & 7) * 2, pack_bf16(acc[32 + 4 * t + 2 * rr], acc[33 + 4 * t + 2 * rr]));
                }
            }
            { const int row = th * 64 + r + 8 * (c >> 1); sts64(sb + SM_VEXT + (c & 1) * 8192 + row * 64 + ((3u ^ ((row >> 1) & 3)) << 4) + 8, 0x00003F80u, 0u); }
            float p[28];
            phi_project(acc, p, sb);
            feature_map(p, sb + SM_PHIK + th * 8192, sb + SM_PHIK + 16384 + th * 8192, r, c);
            fence_async_smem();
            bar_sync(5, 256);
            float kv[16];
#pragma unroll
            for (int i = 0; i < 16; i++) kv[i] = 0.f;
            fence_regs(kv);
            const uint64_t da = make_desc(sb + SM_PHIK + th * 16384, 8192, 1024, 1), db = make_desc(sb + SM_VEXT + th * 8192, 512, 512, 2);
            WG_FENCE();
#pragma unroll
            for (int kk = 0; kk < 8; kk++) wg_ss_n32_ta1_tb1(kv, da + kk * 128, db + kk * 64, kk);
            WG_COMMIT();
            WG_WAIT(0);
            fence_regs(kv);
            float* dst = &g_kvsum[par][(2 * hp + th) * 2048];
#pragma unroll
            for (int t = 0; t < 4; t++) {
                asm volatile("red.relaxed.gpu.global.add.v2.f32 [%0], {%1,%2};" ::"l"(dst + r * 32 + 8 * t + 2 * c), "f"(kv[4 * t]), "f"(kv[4 * t + 1]) : "memory");
                if (r + 8 < 56) asm volatile("red.relaxed.gpu.global.add.v2.f32 [%0], {%1,%2};" ::"l"(dst + (r + 8) * 32 + 8 * t + 2 * c), "f"(kv[4 * t + 2]), "f"(kv[4 * t + 3]) : "memory");
            }
            bar_sync(1 + wg, 128);
            if ((tid & 127) == 0) flag_signal(&g_cnt_kva[hp * 8]);
        }
    }

    const uint32_t e1 = epoch + 1;
    if (lane < 16) flag_wait(&g_cnt_kv[lane * 8], e1 * 16);
    __syncwarp();
    auto ring_load = [&](int blk) {
        const uint32_t bar = sb + B_RF + 8 * (blk & 7);
        mbar_expect_tx(bar, 16384);
        bulk_g2s(sb + SM_RING + (blk & 7) * 16384, g_kv + blk * 16384, 16384, bar);
    };
    if (tid == 384) {
        fence_async_global();
        for (int s = 0; s < 5; s++) ring_load(s);
    }
    {
        float4 a = __ldcg((const float4*)&g_kn[tid * 4]), b = __ldcg((const float4*)&g_kn[SEQ + tid * 4]);
        float4 d = __ldcg((const float4*)&g_kn[2 * SEQ + tid * 4]), e = __ldcg((const float4*)&g_kn[3 * SEQ + tid * 4]);
        a.x += b.x + d.x + e.x; a.y += b.y + d.y + e.y; a.z += b.z + d.z + e.z; a.w += b.w + d.w + e.w;
        float m = fmaxf(fmaxf(a.x, a.y), fmaxf(a.z, a.w));
        if (!(a.x + a.y + a.z + a.w <= 3.0e38f)) m = 3.0e38f;
        const uint32_t mu = __reduce_max_sync(0xffffffffu, __float_as_uint(m));
        if (lane == 0) sts32(sb + SM_WMAX + warp * 4, mu);
    }
    const float vmax = __uint_as_float(__ldcg(&g_vmax[par]));
    __syncthreads();
    if (tid == 384) { for (int s = 5; s < 8; s++) ring_load(s); }
    const int hh = wg & 1;
    const int tok = tb * 128 + th * 64 + r;
    uint32_t q[2][4];
    bool fast;
    {
        const uint32_t kmax2u = __reduce_max_sync(0xffffffffu, lds32(sb + SM_WMAX + (lane & 15) * 4));
        const uint32_t qa = sb + SM_QEXT + wg * 5120 + r * 80 + c * 4;
#pragma unroll
        for (int kk = 0; kk < 2; kk++) {
            q[kk][0] = lds32(qa + kk * 32); q[kk][1] = lds32(qa + kk * 32 + 640);
            q[kk][2] = lds32(qa + kk * 32 + 16); q[kk][3] = lds32(qa + kk * 32 + 16 + 640);
        }
        if (c >= 2) { q[1][2] = 0u; q[1][3] = 0u; }
        float n0 = 0.f, n1 = 0.f;
#pragma unroll
        for (int kk = 0; kk < 2; kk++)
#pragma unroll
            for (int i = 0; i < 4; i += 2) {
                n0 += bf_lo(q[kk][i]) * bf_lo(q[kk][i]) + bf_hi(q[kk][i]) * bf_hi(q[kk][i]);
                n1 += bf_lo(q[kk][i + 1]) * bf_lo(q[kk][i + 1]) + bf_hi(q[kk][i + 1]) * bf_hi(q[kk][i + 1]);
            }
        n0 += __shfl_xor_sync(0xffffffffu, n0, 1); n0 += __shfl_xor_sync(0xffffffffu, n0, 2);
        n1 += __shfl_xor_sync(0xffffffffu, n1, 1); n1 += __shfl_xor_sync(0xffffffffu, n1, 2);
        const float km = __uint_as_float(kmax2u);
        const float b0 = sqrtf(n0 * km) * 1.001f, b1 = sqrtf(n1 * km) * 1.001f;
        const bool ok = b0 <= 90.f && b1 <= 90.f && vmax <= 1.0e12f;
        uint32_t okall;
        asm volatile("{.reg .pred p, q; setp.ne.b32 p, %1, 0; bar.red.and.pred q, %2, 128, p; selp.b32 %0, 1, 0, q;}" : "=r"(okall) : "r"((uint32_t)ok), "r"(1 + wg) : "memory");
        fast = okall != 0;
        if (fast) {
            if (c == 2) { q[1][2] = pack_bf16(64.f - b0, 1.f); q[1][3] = pack_bf16(64.f - b1, 1.f); }
            if (c == 3) { q[1][2] = 0x00003F80u; q[1][3] = 0x00003F80u; }
        }
    }
    const int otok = tb * 128 + (hp & 1) * 64, ocol = (hp >> 1) * 112;
    auto tail_w_addr = [&](int i) -> uint32_t {
        return i < 2 ? SM_TW + i * 16384 : (i < 10 ? (i - 2) * 16384 : (i < 12 ? SM_TW + (i - 10) * 16384 : (i - 12) * 16384));
    };
    auto tail_w_load = [&](int i) {
        const uint32_t bar = sb + B_TF + 8 * i, dst = sb + tail_w_addr(i);
        const CUtensorMap* tm = i < 7 ? &tmWoA : &tmWoB;
        const int k0 = (i < 7 ? i : i - 7) * 64;
        mbar_expect_tx(bar, 16384);
        tma2d(dst, tm, ocol, k0, bar);
        tma2d(dst + 8192, tm, ocol + 64, k0, bar);
    };
    auto tail_o_load = [&](int i) {
        const uint32_t bar = sb + B_TF + 8 * i;
        mbar_expect_tx(bar, 8192);
        tma2d(sb + SM_TO + (i < 7 ? i : i - 7) * 8192, &tmO, i * 64, otok, bar);
    };

    float o[16];
    {
        uint32_t one = 0x3F803F80u;
        asm volatile("" : "+r"(one));
        float s[64];
        uint32_t p[8][4];
        float m0 = -1.0e30f, m1 = -1.0e30f;
#pragma unroll
        for (int i = 0; i < 16; i++) o[i] = 0.f;
#pragma unroll
        for (int i = 0; i < 64; i++) s[i] = 0.f;
        fence_regs(o); fence_regs(s);
        const uint64_t dk0 = make_desc(sb + SM_RING, 16, 512, 2), dv0 = make_desc(sb + SM_RING + 8192, 512, 512, 2);
        mbar_wait(sb + B_RF, 0);
        WG_FENCE();
        wg_rs_n128_tb0(s, q[0], dk0, 0);
        wg_rs_n128_tb0(s, q[1], dk0 + 2, 1);
        WG_COMMIT();
#pragma unroll 1
        for (int j = 0; j < 16; j++) {
            const uint32_t st = j & 7, nst = (j + 1) & 7;
            WG_WAIT(0);
            fence_regs(s);
            if (fast) {
#pragma unroll
                for (int t = 0; t < 16; t++) {
                    uint32_t r0, r1;
                    if ((PMASK >> t) & 1) {
                        r0 = exp2_pair_fma(s[4 * t], s[4 * t + 1], one);
                        r1 = exp2_pair_fma(s[4 * t + 2], s[4 * t + 3], one);
                    } else {
                        r0 = pack_bf16(ex2(s[4 * t]), ex2(s[4 * t + 1]));
                        r1 = pack_bf16(ex2(s[4 * t + 2]), ex2(s[4 * t + 3]));
                    }
                    p[t >> 1][(t & 1) * 2] = r0; p[t >> 1][(t & 1) * 2 + 1] = r1;
                }
            } else {
                float x0 = m0, x1 = m1;
#pragma unroll
                for (int t = 0; t < 16; t++) {
                    const float sc = ((PMASK >> t) & 1) ? 0.5f : 1.f;
                    x0 = fmaxf(x0, sc * fmaxf(s[4 * t], s[4 * t + 1])); x1 = fmaxf(x1, sc * fmaxf(s[4 * t + 2], s[4 * t + 3]));
                }
                x0 = fmaxf(x0, __shfl_xor_sync(0xffffffffu, x0, 1)); x0 = fmaxf(x0, __shfl_xor_sync(0xffffffffu, x0, 2));
                x1 = fmaxf(x1, __shfl_xor_sync(0xffffffffu, x1, 1)); x1 = fmaxf(x1, __shfl_xor_sync(0xffffffffu, x1, 2));
                const float c0 = ex2(m0 - x0), c1 = ex2(m1 - x1);
                m0 = x0; m1 = x1;
#pragma unroll
                for (int t = 0; t < 4; t++) { o[4 * t] *= c0; o[4 * t + 1] *= c0; o[4 * t + 2] *= c1; o[4 * t + 3] *= c1; }
#pragma unroll
                for (int t = 0; t < 16; t++) {
                    const float sc = ((PMASK >> t) & 1) ? 0.5f : 1.f;
                    p[t >> 1][(t & 1) * 2] = pack_bf16(ex2(fmaf(s[4 * t], sc, -x0)), ex2(fmaf(s[4 * t + 1], sc, -x0)));
                    p[t >> 1][(t & 1) * 2 + 1] = pack_bf16(ex2(fmaf(s[4 * t + 2], sc, -x1)), ex2(fmaf(s[4 * t + 3], sc, -x1)));
                }
            }
            fence_regs(p); fence_regs(o);
            WG_FENCE();
            {
                const uint64_t d = dv0 + (uint64_t)(st * 1024);
#pragma unroll
                for (int kk = 0; kk < 8; kk++) wg_rs_n32_tb1(o, p[kk], d + kk * 64, 1);
            }
            WG_COMMIT();
            if (tid == 384 && j >= 2 && j < 10) { mbar_wait(sb + B_RE + 8 * (j - 2), 0); ring_load(j + 6); }
            if (tid == 128) {
                if (j == 8) {
                    mbar_wait(sb + B_MID, 0);
                    tail_w_load(0); tail_w_load(1);
                    flag_wait(&g_cnt_oa[(tb * 2 + (hp & 1)) * 8], e1 * 16);
                    fence_async_global();
                    for (int i = 0; i < 7; i++) tail_o_load(i);
                }
                if (j >= 10) { mbar_wait(sb + B_RE + 8 * (j - 10), 1); tail_w_load(j - 8); }
            }
            if (j < 15) mbar_wait(sb + B_RF + 8 * nst, (j + 1) >> 3);
            WG_WAIT(0);
            fence_regs(o);
            if (lane == 0) mbar_arrive(sb + B_RE + 8 * st);
            if (j == MID) {
                if (lane == 0) flag_wait(&g_cnt_kva[hp * 8], e1 * 32);
                __syncwarp();
                const int t = tid & 127, fi = t >> 1;
                const float4* src = (const float4*)&g_kvsum[par][(2 * hp + hh) * 2048 + t * 16];
                const float4 a0 = __ldcg(src), a1 = __ldcg(src + 1), a2 = __ldcg(src + 2), a3 = __ldcg(src + 3);
                const float g0 = __ldcg(&g_gate[tok]), g1 = __ldcg(&g_gate[tok + 8]);
                const uint32_t kb = sb + SM_KVX + wg * 4096 + fi * 64, sw = (fi >> 1) & 3;
                sts128(kb + ((((t & 1) * 2) ^ sw) << 4), pack_bf16(a0.x, a0.y), pack_bf16(a0.z, a0.w), pack_bf16(a1.x, a1.y), pack_bf16(a1.z, a1.w));
                sts128(kb + ((((t & 1) * 2 + 1) ^ sw) << 4), pack_bf16(a2.x, a2.y), pack_bf16(a2.z, a2.w), pack_bf16(a3.x, a3.y), pack_bf16(a3.z, a3.w));
                fence_async_smem();
                bar_sync(1 + wg, 128);
                float nm[16];
#pragma unroll
                for (int i = 0; i < 16; i++) nm[i] = 0.f;
                fence_regs(nm);
                const uint64_t da = make_desc(sb + SM_PHIQ + (hh * 2 + th) * 8192, 16, 1024, 1), db = make_desc(sb + SM_KVX + wg * 4096, 512, 512, 2);
                WG_FENCE();
#pragma unroll
                for (int kk = 0; kk < 4; kk++) wg_ss_n32_ta0_tb1(nm, da + kk * 2, db + kk * 64, kk);
                WG_COMMIT();
                WG_WAIT(0);
                fence_regs(nm);
                if (lane == 0) mbar_arrive(sb + B_MID);
                const float d0 = __shfl_sync(0xffffffffu, nm[12], (lane & ~3) | 2) + 1e-6f, d1 = __shfl_sync(0xffffffffu, nm[14], (lane & ~3) | 2) + 1e-6f;
                const float s0 = g0 / d0, s1 = g1 / d1;
                uint32_t* dst = (uint32_t*)(g_ocat + (size_t)tok * 896 + (2 * hp + hh) * 28 + 2 * c);
#pragma unroll
                for (int t4 = 0; t4 < 4; t4++)
                    if (t4 < 3 || c < 2) {
                        dst[4 * t4] = pack_bf16(nm[4 * t4] * s0, nm[4 * t4 + 1] * s0);
                        dst[4 * t4 + 8 * 448] = pack_bf16(nm[4 * t4 + 2] * s1, nm[4 * t4 + 3] * s1);
                    }
                bar_sync(1 + wg, 128);
                if ((tid & 127) == 0) flag_signal(&g_cnt_oa[(tb * 2 + th) * 8]);
            }
            {
                const uint64_t d = dk0 + (uint64_t)((j < 15 ? nst : st) * 1024);
                WG_FENCE();
                wg_rs_n128_tb0(s, q[0], d, 0);
                wg_rs_n128_tb0(s, q[1], d + 2, 1);
                WG_COMMIT();
            }
        }
        WG_WAIT(0);
        fence_regs(s);
    }
    {
        const float g0 = __ldcg(&g_gate[tok]), g1 = __ldcg(&g_gate[tok + 8]);
        const float l0 = __shfl_sync(0xffffffffu, o[12], (lane & ~3) | 2), l1 = __shfl_sync(0xffffffffu, o[14], (lane & ~3) | 2);
        const float s0 = (1.f - g0) / l0, s1 = (1.f - g1) / l1;
        uint32_t* dst = (uint32_t*)(g_ocat + (size_t)tok * 896 + 448 + (2 * hp + hh) * 28 + 2 * c);
#pragma unroll
        for (int t4 = 0; t4 < 4; t4++)
            if (t4 < 3 || c < 2) {
                dst[4 * t4] = pack_bf16(o[4 * t4] * s0, o[4 * t4 + 1] * s0);
                dst[4 * t4 + 8 * 448] = pack_bf16(o[4 * t4 + 2] * s1, o[4 * t4 + 3] * s1);
            }
        bar_sync(1 + wg, 128);
        if ((tid & 127) == 0) flag_signal(&g_cnt_ob[(tb * 2 + th) * 8]);
    }

    if (wg == 0) {
        float acc[56];
#pragma unroll
        for (int i = 0; i < 56; i++) acc[i] = 0.f;
        fence_regs(acc);
#pragma unroll
        for (int i = 0; i < 14; i++) {
            mbar_wait(sb + B_TF + 8 * i, 0);
            const uint64_t da = make_desc(sb + SM_TO + (i < 7 ? i : i - 7) * 8192, 16, 1024, 1), db = make_desc(sb + tail_w_addr(i), 8192, 1024, 1);
            WG_FENCE();
#pragma unroll
            for (int kk = 0; kk < 4; kk++) wg_ss_n112_ta0_tb1(acc, da + kk * 2, db + kk * 128, (i | kk) != 0);
            WG_COMMIT();
            if (i >= 1 && i <= 6) {
                WG_WAIT(1);
                if (lane == 0) mbar_arrive(sb + B_TD + 8 * (i - 1));
            }
            if (i == 6) { WG_WAIT(0); if (lane == 0) mbar_arrive(sb + B_TD + 8 * 6); }
        }
        WG_WAIT(0);
        fence_regs(acc);
        uint32_t* dst = (uint32_t*)(out + (size_t)(otok + r) * DM + ocol + 2 * c);
#pragma unroll
        for (int t = 0; t < 14; t++) {
            dst[4 * t] = pack_bf16(acc[4 * t], acc[4 * t + 1]);
            dst[4 * t + 8 * 224] = pack_bf16(acc[4 * t + 2], acc[4 * t + 3]);
        }
        if (tid == 0) {
            const uint32_t d = atomicAdd(&g_done, 1u);
            if (d + 1 == e1 * 128) *(volatile uint32_t*)&g_epoch = e1;
        }
    } else if (tid == 128) {
        mbar_wait(sb + B_RE + 8 * 6, 1); tail_w_load(8);
        mbar_wait(sb + B_RE + 8 * 7, 1); tail_w_load(9);
        for (int i = 0; i < 4; i++) { mbar_wait(sb + B_TD + 8 * i, 0); tail_w_load(10 + i); }
    } else if (tid == 256) {
        flag_wait(&g_cnt_ob[(tb * 2 + (hp & 1)) * 8], e1 * 16);
        fence_async_global();
        for (int i = 0; i < 7; i++) { mbar_wait(sb + B_TD + 8 * i, 0); tail_o_load(7 + i); }
    }
}

typedef CUresult (*EncodeFn)(CUtensorMap*, CUtensorMapDataType, cuuint32_t, void*, const cuuint64_t*, const cuuint64_t*, const cuuint32_t*,
                             const cuuint32_t*, CUtensorMapInterleave, CUtensorMapSwizzle, CUtensorMapL2promotion, CUtensorMapFloatOOBfill);

void make_map(EncodeFn enc, CUtensorMap* tm, const void* ptr, uint64_t cols, uint64_t rows, uint32_t bc, uint32_t br) {
    cuuint64_t gd[2] = {cols, rows}, gs[1] = {cols * 2};
    cuuint32_t box[2] = {bc, br}, es[2] = {1, 1};
    enc(tm, CU_TENSOR_MAP_DATA_TYPE_BFLOAT16, 2, (void*)ptr, gd, gs, box, es, CU_TENSOR_MAP_INTERLEAVE_NONE, CU_TENSOR_MAP_SWIZZLE_128B,
        CU_TENSOR_MAP_L2_PROMOTION_L2_256B, CU_TENSOR_MAP_FLOAT_OOB_FILL_NONE);
}

}

extern "C" void kernel_launch(void* const* d_in, const int* in_sizes, int n_in, void* d_out, int out_size) {
    (void)in_sizes; (void)n_in; (void)out_size;
    static EncodeFn enc = nullptr;
    static void* ocat = nullptr;
    if (!enc) {
        void* fn = nullptr;
        cudaDriverEntryPointQueryResult qr;
        cudaGetDriverEntryPoint("cuTensorMapEncodeTiled", &fn, cudaEnableDefault, &qr);
        enc = (EncodeFn)fn;
        cudaGetSymbolAddress(&ocat, g_ocat);
        cudaFuncSetAttribute(fused_kernel, cudaFuncAttributeMaxDynamicSharedMemorySize, SM_TOTAL);
    }
    CUtensorMap tmX, tmWqkv, tmWq, tmWoA, tmWoB, tmO;
    make_map(enc, &tmX, d_in[0], 448, 2048, 64, 128);
    make_map(enc, &tmWqkv, d_in[1], 1344, 448, 56, 64);
    make_map(enc, &tmWq, d_in[5], 448, 448, 56, 64);
    make_map(enc, &tmWoA, d_in[3], 448, 448, 64, 64);
    make_map(enc, &tmWoB, d_in[8], 448, 448, 64, 64);
    make_map(enc, &tmO, ocat, 896, 2048, 64, 64);
    fused_kernel<<<128, 512, SM_TOTAL>>>(tmX, tmWqkv, tmWq, tmWoA, tmWoB, tmO, (const __nv_bfloat16*)d_in[2], (const __nv_bfloat16*)d_in[6],
                                         (const __nv_bfloat16*)d_in[7], (const __nv_bfloat16*)d_in[9], (__nv_bfloat16*)d_out);
}
```

```cpp
#include <cuda_runtime.h>
#include <cuda_bf16.h>
#include <cuda.h>
#include <stdint.h>

namespace {

constexpr int SEQ = 2048;
constexpr uint32_t PMASK = 0xB6DAu;
constexpr int MID = 6;

constexpr uint32_t SM_X = 0;
constexpr uint32_t SM_W = 114688;
constexpr uint32_t SM_RING = 0;
constexpr uint32_t SM_PHIK = 0;
constexpr uint32_t SM_VEXT = 32768;
constexpr uint32_t SM_PHIQ = 131072;
constexpr uint32_t SM_KVX = 163840;
constexpr uint32_t SM_WPHI = 196608;
constexpr uint32_t SM_SW = 204800;
constexpr uint32_t SM_QEXT = 204800;
constexpr uint32_t SM_SL = 217088;
constexpr uint32_t SM_Q0 = 221184;
constexpr uint32_t SM_TO = 131072;
constexpr uint32_t SM_TW = 188416;
constexpr uint32_t SM_OST = 204800;
constexpr uint32_t SM_KVS = 180224;
constexpr uint32_t SM_BAR = 229376;
constexpr uint32_t B_RF = SM_BAR, B_RE = SM_BAR + 64, B_TF = SM_BAR + 128  , B_TD = SM_BAR + 248  , B_MID = SM_BAR + 304, B_KVR = SM_BAR + 312,
                   B_KVS = SM_BAR + 320, B_P1F = SM_BAR + 328  ,
                   B_P1E = SM_BAR + 440  , B_SKV = B_P1E + 80, B_SKVA = B_SKV + 8, B_SOA = B_SKV + 16, B_WPR = B_SKV + 48,
                   B_QRD = B_SKV + 56  ,
                   B_OAD = SM_BAR + 584  , B_QLD = SM_BAR + 600, B_TOB = SM_BAR + 608  ,
                   SM_WMAX = SM_BAR + 672  , SM_KMAX = SM_BAR + 736  ,
                   SM_GATE = SM_BAR + 768  ;
constexpr uint32_t B_XF = SM_BAR + 1280  , B_SOW = SM_BAR + 1336  , B_REL = SM_BAR + 1368, B_KVX = SM_BAR + 1376  ;
constexpr uint32_t SM_TOTAL = SM_BAR + 1408 + 1024;

__device__ __align__(1024) __nv_bfloat16 g_kv[16 * 256 * 32];
__device__ __align__(16) float g_gate[SEQ];
__device__ __align__(16) float g_kvsum[2][16 * 2048];
__device__ __align__(1024) __nv_bfloat16 g_ocat[SEQ * 448];
__device__ __align__(1024) uint8_t g_ob[32 * 8 * 8192];
__device__ __align__(128) uint64_t g_f_kv[128];
__device__ __align__(128) uint32_t g_f_kva[8 * 32], g_f_oa[32 * 8], g_f_ob[32 * 16];
__device__ uint32_t g_epoch, g_done;

__device__ __forceinline__ uint64_t make_desc(uint32_t saddr, uint32_t lbo, uint32_t sbo, uint32_t swz) {
    return (uint64_t)((saddr & 0x3FFFF) >> 4) | ((uint64_t)(lbo >> 4) << 16) | ((uint64_t)(sbo >> 4) << 32) | ((uint64_t)swz << 62);
}
#define WG_FENCE() asm volatile("wgmma.fence.sync.aligned;" ::: "memory")
#define WG_COMMIT() asm volatile("wgmma.commit_group.sync.aligned;" ::: "memory")
#define WG_WAIT(n) asm volatile("wgmma.wait_group.sync.aligned %0;" ::"n"(n) : "memory")
template <int N> __device__ __forceinline__ void fence_regs(float (&r)[N]) {
#pragma unroll
    for (int i = 0; i < N; i++) asm volatile("" : "+f"(r[i])::"memory");
}
template <int N> __device__ __forceinline__ void fence_regs(uint32_t (&r)[N][4]) {
#pragma unroll
    for (int i = 0; i < N; i++) asm volatile("" : "+r"(r[i][0]), "+r"(r[i][1]), "+r"(r[i][2]), "+r"(r[i][3])::"memory");
}
__device__ __forceinline__ void mbar_init(uint32_t bar, uint32_t cnt) { asm volatile("mbarrier.init.shared::cta.b64 [%0], %1;" ::"r"(bar), "r"(cnt) : "memory"); }
__device__ __forceinline__ void mbar_expect_tx(uint32_t bar, uint32_t bytes) { asm volatile("mbarrier.arrive.expect_tx.shared::cta.b64 _, [%0], %1;" ::"r"(bar), "r"(bytes) : "memory"); }
__device__ __forceinline__ void mbar_arrive(uint32_t bar) { asm volatile("mbarrier.arrive.shared::cta.b64 _, [%0];" ::"r"(bar) : "memory"); }
__device__ __forceinline__ bool mbar_try(uint32_t bar, uint32_t parity) {
    uint32_t ok;
    asm volatile("{.reg .pred p; mbarrier.try_wait.parity.shared::cta.b64 p, [%1], %2; selp.b32 %0, 1, 0, p;}" : "=r"(ok) : "r"(bar), "r"(parity) : "memory");
    return ok;
}
__device__ __forceinline__ void mbar_wait(uint32_t bar, uint32_t parity) {
    asm volatile("{\n.reg .pred p;\n.reg .b32 n;\nmov.b32 n, 0x100000;\n"
                 "W_%=:\nmbarrier.try_wait.parity.shared::cta.b64 p, [%0], %1;\n@p bra D_%=;\n"
                 "add.s32 n, n, -1;\nsetp.ne.b32 p, n, 0;\n@p bra W_%=;\nD_%=:\n}" ::"r"(bar), "r"(parity) : "memory");
}
#define mbar_wait_svc mbar_wait
__device__ __forceinline__ void mbar_wait_cluster(uint32_t bar) {
    asm volatile("{\n.reg .pred p;\n.reg .b32 n;\nmov.b32 n, 0x100000;\n"
                 "W_%=:\nmbarrier.try_wait.parity.acquire.cluster.shared::cta.b64 p, [%0], 0;\n@p bra D_%=;\n"
                 "add.s32 n, n, -1;\nsetp.ne.b32 p, n, 0;\n@p bra W_%=;\nD_%=:\n}" ::"r"(bar) : "memory");
}
__device__ __forceinline__ uint32_t ld_relaxed(const uint32_t* p) { uint32_t v; asm volatile("ld.relaxed.gpu.global.u32 %0, [%1];" : "=r"(v) : "l"(p) : "memory"); return v; }
__device__ __forceinline__ void prefetch_map(const CUtensorMap* tm) { asm volatile("prefetch.tensormap [%0];" ::"l"(tm) : "memory"); }
__device__ __forceinline__ void flags_wait(const uint32_t* p, int n, uint32_t tag, int lane) {
    bool ok = lane >= n;
    for (uint32_t it = 0; it < (1u << 18); it++) {
        if (!ok) ok = ld_relaxed(p + lane) == tag;
        if (__all_sync(0xffffffffu, ok)) break;
    }
    asm volatile("fence.acquire.gpu;\n\tfence.proxy.async.global;" ::: "memory");
}
__device__ __forceinline__ void flag_set(uint32_t* p, uint32_t tag) {
    asm volatile("st.release.gpu.global.u32 [%0], %1;" ::"l"(p), "r"(tag) : "memory");
}
__device__ __forceinline__ void tma2d_store(const CUtensorMap* tm, uint32_t src, int c0, int c1) {
    asm volatile("cp.async.bulk.tensor.2d.global.shared::cta.bulk_group [%0, {%2, %3}], [%1];\n\tcp.async.bulk.commit_group;" ::"l"(tm), "r"(src), "r"(c0), "r"(c1) : "memory");
}
__device__ __forceinline__ void fence_async_smem() { asm volatile("fence.proxy.async.shared::cta;" ::: "memory"); }
__device__ __forceinline__ void bar_sync(int id, int n) { asm volatile("bar.sync %0, %1;" ::"r"(id), "r"(n) : "memory"); }
__device__ __forceinline__ void bulk_g2s(uint32_t dst, const void* src, uint32_t bytes, uint32_t bar) {
    asm volatile("cp.async.bulk.shared::cluster.global.mbarrier::complete_tx::bytes [%0], [%1], %2, [%3];" ::"r"(dst), "l"(src), "r"(bytes), "r"(bar) : "memory");
}
__device__ __forceinline__ void tma2d(uint32_t dst, const CUtensorMap* tm, int c0, int c1, uint32_t bar) {
    asm volatile("cp.async.bulk.tensor.2d.shared::cluster.global.mbarrier::complete_tx::bytes [%0], [%1, {%3, %4}], [%2];" ::"r"(dst), "l"(tm), "r"(bar), "r"(c0), "r"(c1) : "memory");
}
__device__ __forceinline__ void tma3d(uint32_t dst, const CUtensorMap* tm, int c0, int c1, int c2, uint32_t bar) {
    asm volatile("cp.async.bulk.tensor.3d.shared::cluster.global.mbarrier::complete_tx::bytes [%0], [%1, {%3, %4, %5}], [%2];" ::"r"(dst), "l"(tm), "r"(bar), "r"(c0), "r"(c1), "r"(c2) : "memory");
}
__device__ __forceinline__ void tma2d_mc(uint32_t dst, const CUtensorMap* tm, int c0, int c1, uint32_t bar) {
    asm volatile("cp.async.bulk.tensor.2d.shared::cluster.global.mbarrier::complete_tx::bytes.multicast::cluster [%0], [%1, {%3, %4}], [%2], %5;" ::"r"(dst), "l"(tm), "r"(bar), "r"(c0), "r"(c1), "h"((uint16_t)3) : "memory");
}
__device__ __forceinline__ void mbar_arrive_both(uint32_t bar, uint32_t peer) {
    asm volatile("{.reg .b32 ra; mapa.shared::cluster.u32 ra, %0, %1;\n\tmbarrier.arrive.shared::cluster.b64 _, [ra];\n\t"
                 "mbarrier.arrive.shared::cta.b64 _, [%0];}" ::"r"(bar), "r"(peer) : "memory");
}
__device__ __forceinline__ void sts32(uint32_t a, uint32_t v) { asm volatile("st.shared.b32 [%0], %1;" ::"r"(a), "r"(v) : "memory"); }
__device__ __forceinline__ void sts64(uint32_t a, uint32_t v0, uint32_t v1) { asm volatile("st.shared.v2.b32 [%0], {%1,%2};" ::"r"(a), "r"(v0), "r"(v1) : "memory"); }
__device__ __forceinline__ void sts128(uint32_t a, uint32_t v0, uint32_t v1, uint32_t v2, uint32_t v3) { asm volatile("st.shared.v4.b32 [%0], {%1,%2,%3,%4};" ::"r"(a), "r"(v0), "r"(v1), "r"(v2), "r"(v3) : "memory"); }
__device__ __forceinline__ uint32_t lds32(uint32_t a) { uint32_t v; asm volatile("ld.shared.b32 %0, [%1];" : "=r"(v) : "r"(a) : "memory"); return v; }
__device__ __forceinline__ float ex2(float x) { float r; asm("ex2.approx.ftz.f32 %0, %1;" : "=f"(r) : "f"(x)); return r; }
__device__ __forceinline__ float rcp(float x) { float r; asm("rcp.approx.ftz.f32 %0, %1;" : "=f"(r) : "f"(x)); return r; }
__device__ __forceinline__ uint32_t pack_bf16(float lo, float hi) { uint32_t r; asm("cvt.rn.bf16x2.f32 %0, %1, %2;" : "=r"(r) : "f"(hi), "f"(lo)); return r; }
__device__ __forceinline__ float bf_lo(uint32_t v) { return __uint_as_float(v << 16); }
__device__ __forceinline__ float bf_hi(uint32_t v) { return __uint_as_float(v & 0xFFFF0000u); }
__device__ __forceinline__ uint32_t hfma(uint32_t a, uint32_t b, uint32_t c) { uint32_t r; asm("fma.rn.bf16x2 %0, %1, %2, %3;" : "=r"(r) : "r"(a), "r"(b), "r"(c)); return r; }

__device__ __forceinline__ void wg_ss_n120_ta0_tb1(float (&d)[60], uint64_t ad, uint64_t bd, int sc) {
    asm volatile("{.reg .pred p; setp.ne.b32 p, %62, 0;\n"
        "wgmma.mma_async.sync.aligned.m64n120k16.f32.bf16.bf16 {%0,%1,%2,%3,%4,%5,%6,%7,%8,%9,%10,%11,%12,%13,%14,%15,%16,%17,%18,%19,%20,%21,%22,%23,%24,%25,%26,%27,%28,%29,%30,%31,%32,%33,%34,%35,%36,%37,%38,%39,%40,%41,%42,%43,%44,%45,%46,%47,%48,%49,%50,%51,%52,%53,%54,%55,%56,%57,%58,%59}, %60, %61, p, 1, 1, 0, 1;}"
        : "+f"(d[0]),"+f"(d[1]),"+f"(d[2]),"+f"(d[3]),"+f"(d[4]),"+f"(d[5]),"+f"(d[6]),"+f"(d[7]),
          "+f"(d[8]),"+f"(d[9]),"+f"(d[10]),"+f"(d[11]),"+f"(d[12]),"+f"(d[13]),"+f"(d[14]),"+f"(d[15]),
          "+f"(d[16]),"+f"(d[17]),"+f"(d[18]),"+f"(d[19]),"+f"(d[20]),"+f"(d[21]),"+f"(d[22]),"+f"(d[23]),
          "+f"(d[24]),"+f"(d[25]),"+f"(d[26]),"+f"(d[27]),"+f"(d[28]),"+f"(d[29]),"+f"(d[30]),"+f"(d[31]),
          "+f"(d[32]),"+f"(d[33]),"+f"(d[34]),"+f"(d[35]),"+f"(d[36]),"+f"(d[37]),"+f"(d[38]),"+f"(d[39]),
          "+f"(d[40]),"+f"(d[41]),"+f"(d[42]),"+f"(d[43]),"+f"(d[44]),"+f"(d[45]),"+f"(d[46]),"+f"(d[47]),
          "+f"(d[48]),"+f"(d[49]),"+f"(d[50]),"+f"(d[51]),"+f"(d[52]),"+f"(d[53]),"+f"(d[54]),"+f"(d[55]),
          "+f"(d[56]),"+f"(d[57]),"+f"(d[58]),"+f"(d[59])
        : "l"(ad), "l"(bd), "r"(sc));
}
__device__ __forceinline__ void wg_rs_n56_tb1(float (&d)[28], const uint32_t (&a)[4], uint64_t bd, int sc) {
    asm volatile("{.reg .pred p; setp.ne.b32 p, %33, 0;\n"
        "wgmma.mma_async.sync.aligned.m64n56k16.f32.bf16.bf16 {%0,%1,%2,%3,%4,%5,%6,%7,%8,%9,%10,%11,%12,%13,%14,%15,%16,%17,%18,%19,%20,%21,%22,%23,%24,%25,%26,%27}, {%28,%29,%30,%31}, %32, p, 1, 1, 1;}"
        : "+f"(d[0]),"+f"(d[1]),"+f"(d[2]),"+f"(d[3]),"+f"(d[4]),"+f"(d[5]),"+f"(d[6]),"+f"(d[7]),
          "+f"(d[8]),"+f"(d[9]),"+f"(d[10]),"+f"(d[11]),"+f"(d[12]),"+f"(d[13]),"+f"(d[14]),"+f"(d[15]),
          "+f"(d[16]),"+f"(d[17]),"+f"(d[18]),"+f"(d[19]),"+f"(d[20]),"+f"(d[21]),"+f"(d[22]),"+f"(d[23]),
          "+f"(d[24]),"+f"(d[25]),"+f"(d[26]),"+f"(d[27])
        : "r"(a[0]),"r"(a[1]),"r"(a[2]),"r"(a[3]), "l"(bd), "r"(sc));
}
__device__ __forceinline__ void wg_ss_n32_ta1_tb1(float (&d)[16], uint64_t ad, uint64_t bd, int sc) {
    asm volatile("{.reg .pred p; setp.ne.b32 p, %18, 0;\n"
        "wgmma.mma_async.sync.aligned.m64n32k16.f32.bf16.bf16 {%0,%1,%2,%3,%4,%5,%6,%7,%8,%9,%10,%11,%12,%13,%14,%15}, %16, %17, p, 1, 1, 1, 1;}"
        : "+f"(d[0]),"+f"(d[1]),"+f"(d[2]),"+f"(d[3]),"+f"(d[4]),"+f"(d[5]),"+f"(d[6]),"+f"(d[7]),
          "+f"(d[8]),"+f"(d[9]),"+f"(d[10]),"+f"(d[11]),"+f"(d[12]),"+f"(d[13]),"+f"(d[14]),"+f"(d[15])
        : "l"(ad), "l"(bd), "r"(sc));
}
__device__ __forceinline__ void wg_ss_n32_ta0_tb1(float (&d)[16], uint64_t ad, uint64_t bd, int sc) {
    asm volatile("{.reg .pred p; setp.ne.b32 p, %18, 0;\n"
        "wgmma.mma_async.sync.aligned.m64n32k16.f32.bf16.bf16 {%0,%1,%2,%3,%4,%5,%6,%7,%8,%9,%10,%11,%12,%13,%14,%15}, %16, %17, p, 1, 1, 0, 1;}"
        : "+f"(d[0]),"+f"(d[1]),"+f"(d[2]),"+f"(d[3]),"+f"(d[4]),"+f"(d[5]),"+f"(d[6]),"+f"(d[7]),
          "+f"(d[8]),"+f"(d[9]),"+f"(d[10]),"+f"(d[11]),"+f"(d[12]),"+f"(d[13]),"+f"(d[14]),"+f"(d[15])
        : "l"(ad), "l"(bd), "r"(sc));
}
__device__ __forceinline__ void wg_rs_n128_tb0(float (&d)[64], const uint32_t (&a)[4], uint64_t bd, int sc) {
    asm volatile("{.reg .pred p; setp.ne.b32 p, %69, 0;\n"
        "wgmma.mma_async.sync.aligned.m64n128k16.f32.bf16.bf16 {%0,%1,%2,%3,%4,%5,%6,%7,%8,%9,%10,%11,%12,%13,%14,%15,%16,%17,%18,%19,%20,%21,%22,%23,%24,%25,%26,%27,%28,%29,%30,%31,%32,%33,%34,%35,%36,%37,%38,%39,%40,%41,%42,%43,%44,%45,%46,%47,%48,%49,%50,%51,%52,%53,%54,%55,%56,%57,%58,%59,%60,%61,%62,%63}, {%64,%65,%66,%67}, %68, p, 1, 1, 0;}"
        : "+f"(d[0]),"+f"(d[1]),"+f"(d[2]),"+f"(d[3]),"+f"(d[4]),"+f"(d[5]),"+f"(d[6]),"+f"(d[7]),
          "+f"(d[8]),"+f"(d[9]),"+f"(d[10]),"+f"(d[11]),"+f"(d[12]),"+f"(d[13]),"+f"(d[14]),"+f"(d[15]),
          "+f"(d[16]),"+f"(d[17]),"+f"(d[18]),"+f"(d[19]),"+f"(d[20]),"+f"(d[21]),"+f"(d[22]),"+f"(d[23]),
          "+f"(d[24]),"+f"(d[25]),"+f"(d[26]),"+f"(d[27]),"+f"(d[28]),"+f"(d[29]),"+f"(d[30]),"+f"(d[31]),
          "+f"(d[32]),"+f"(d[33]),"+f"(d[34]),"+f"(d[35]),"+f"(d[36]),"+f"(d[37]),"+f"(d[38]),"+f"(d[39]),
          "+f"(d[40]),"+f"(d[41]),"+f"(d[42]),"+f"(d[43]),"+f"(d[44]),"+f"(d[45]),"+f"(d[46]),"+f"(d[47]),
          "+f"(d[48]),"+f"(d[49]),"+f"(d[50]),"+f"(d[51]),"+f"(d[52]),"+f"(d[53]),"+f"(d[54]),"+f"(d[55]),
          "+f"(d[56]),"+f"(d[57]),"+f"(d[58]),"+f"(d[59]),"+f"(d[60]),"+f"(d[61]),"+f"(d[62]),"+f"(d[63])
        : "r"(a[0]),"r"(a[1]),"r"(a[2]),"r"(a[3]), "l"(bd), "r"(sc));
}
__device__ __forceinline__ void wg_rs_n32_tb1(float (&d)[16], const uint32_t (&a)[4], uint64_t bd, int sc) {
    asm volatile("{.reg .pred p; setp.ne.b32 p, %21, 0;\n"
        "wgmma.mma_async.sync.aligned.m64n32k16.f32.bf16.bf16 {%0,%1,%2,%3,%4,%5,%6,%7,%8,%9,%10,%11,%12,%13,%14,%15}, {%16,%17,%18,%19}, %20, p, 1, 1, 1;}"
        : "+f"(d[0]),"+f"(d[1]),"+f"(d[2]),"+f"(d[3]),"+f"(d[4]),"+f"(d[5]),"+f"(d[6]),"+f"(d[7]),
          "+f"(d[8]),"+f"(d[9]),"+f"(d[10]),"+f"(d[11]),"+f"(d[12]),"+f"(d[13]),"+f"(d[14]),"+f"(d[15])
        : "r"(a[0]),"r"(a[1]),"r"(a[2]),"r"(a[3]), "l"(bd), "r"(sc));
}
__device__ __forceinline__ void wg_ss_n64_ta0_tb1(float (&d)[32], uint64_t ad, uint64_t bd, int sc) {
    asm volatile("{.reg .pred p; setp.ne.b32 p, %34, 0;\n"
        "wgmma.mma_async.sync.aligned.m64n64k16.f32.bf16.bf16 {%0,%1,%2,%3,%4,%5,%6,%7,%8,%9,%10,%11,%12,%13,%14,%15,%16,%17,%18,%19,%20,%21,%22,%23,%24,%25,%26,%27,%28,%29,%30,%31}, %32, %33, p, 1, 1, 0, 1;}"
        : "+f"(d[0]),"+f"(d[1]),"+f"(d[2]),"+f"(d[3]),"+f"(d[4]),"+f"(d[5]),"+f"(d[6]),"+f"(d[7]),
          "+f"(d[8]),"+f"(d[9]),"+f"(d[10]),"+f"(d[11]),"+f"(d[12]),"+f"(d[13]),"+f"(d[14]),"+f"(d[15]),
          "+f"(d[16]),"+f"(d[17]),"+f"(d[18]),"+f"(d[19]),"+f"(d[20]),"+f"(d[21]),"+f"(d[22]),"+f"(d[23]),
          "+f"(d[24]),"+f"(d[25]),"+f"(d[26]),"+f"(d[27]),"+f"(d[28]),"+f"(d[29]),"+f"(d[30]),"+f"(d[31])
        : "l"(ad), "l"(bd), "r"(sc));
}
__device__ __forceinline__ void wg_ss_n8_ta0_tb1(float (&d)[4], uint64_t ad, uint64_t bd, int sc) {
    asm volatile("{.reg .pred p; setp.ne.b32 p, %6, 0;\n"
        "wgmma.mma_async.sync.aligned.m64n8k16.f32.bf16.bf16 {%0,%1,%2,%3}, %4, %5, p, 1, 1, 0, 1;}"
        : "+f"(d[0]),"+f"(d[1]),"+f"(d[2]),"+f"(d[3])
        : "l"(ad), "l"(bd), "r"(sc));
}
__device__ __forceinline__ void wg_ss_n128_ta0_tb0(float (&d)[64], uint64_t ad, uint64_t bd, int sc) {
    asm volatile("{.reg .pred p; setp.ne.b32 p, %66, 0;\n"
        "wgmma.mma_async.sync.aligned.m64n128k16.f32.bf16.bf16 {%0,%1,%2,%3,%4,%5,%6,%7,%8,%9,%10,%11,%12,%13,%14,%15,%16,%17,%18,%19,%20,%21,%22,%23,%24,%25,%26,%27,%28,%29,%30,%31,%32,%33,%34,%35,%36,%37,%38,%39,%40,%41,%42,%43,%44,%45,%46,%47,%48,%49,%50,%51,%52,%53,%54,%55,%56,%57,%58,%59,%60,%61,%62,%63}, %64, %65, p, 1, 1, 0, 0;}"
        : "+f"(d[0]),"+f"(d[1]),"+f"(d[2]),"+f"(d[3]),"+f"(d[4]),"+f"(d[5]),"+f"(d[6]),"+f"(d[7]),
          "+f"(d[8]),"+f"(d[9]),"+f"(d[10]),"+f"(d[11]),"+f"(d[12]),"+f"(d[13]),"+f"(d[14]),"+f"(d[15]),
          "+f"(d[16]),"+f"(d[17]),"+f"(d[18]),"+f"(d[19]),"+f"(d[20]),"+f"(d[21]),"+f"(d[22]),"+f"(d[23]),
          "+f"(d[24]),"+f"(d[25]),"+f"(d[26]),"+f"(d[27]),"+f"(d[28]),"+f"(d[29]),"+f"(d[30]),"+f"(d[31]),
          "+f"(d[32]),"+f"(d[33]),"+f"(d[34]),"+f"(d[35]),"+f"(d[36]),"+f"(d[37]),"+f"(d[38]),"+f"(d[39]),
          "+f"(d[40]),"+f"(d[41]),"+f"(d[42]),"+f"(d[43]),"+f"(d[44]),"+f"(d[45]),"+f"(d[46]),"+f"(d[47]),
          "+f"(d[48]),"+f"(d[49]),"+f"(d[50]),"+f"(d[51]),"+f"(d[52]),"+f"(d[53]),"+f"(d[54]),"+f"(d[55]),
          "+f"(d[56]),"+f"(d[57]),"+f"(d[58]),"+f"(d[59]),"+f"(d[60]),"+f"(d[61]),"+f"(d[62]),"+f"(d[63])
        : "l"(ad), "l"(bd), "r"(sc));
}


__device__ __forceinline__ uint32_t exp2_pair_fma(float y0, float y1, uint32_t one) {
    uint32_t e = __byte_perm(__float_as_uint(y0), __float_as_uint(y1), 0x6521);
    uint32_t m;
    asm("lop3.b32 %0, %1, 0x007F007F, %2, 0xEA;" : "=r"(m) : "r"(e), "r"(one));
    uint32_t t = hfma(m, 0x3EAC3EACu, 0xBC66BC66u);
    t = hfma(t, m, 0x3F2E3F2Eu);
    return e + t - m;
}

template <bool NORM>
__device__ __forceinline__ void feature_map(float (&p)[28], uint32_t (&f)[2][7], uint32_t (&g)[2][7], int c) {
    const float L2E = 1.4426950408889634f;
    const bool lo = c < 2;
    float mx0[2], mn0[2], mx1[2], mn1[2];
#pragma unroll
    for (int rr = 0; rr < 2; rr++) {
        const float* x = p + 2 * rr;
        mx0[rr] = fmaxf(fmaxf(fmaxf(x[0], x[1]), fmaxf(x[4], x[5])), fmaxf(x[8], x[9]));
        mn0[rr] = fminf(fminf(fminf(x[0], x[1]), fminf(x[4], x[5])), fminf(x[8], x[9]));
        mx1[rr] = fmaxf(fmaxf(fmaxf(x[16], x[17]), fmaxf(x[20], x[21])), fmaxf(x[24], x[25]));
        mn1[rr] = fminf(fminf(fminf(x[16], x[17]), fminf(x[20], x[21])), fminf(x[24], x[25]));
        const float mx3 = fmaxf(x[12], x[13]), mn3 = fminf(x[12], x[13]);
        if (lo) { mx0[rr] = fmaxf(mx0[rr], mx3); mn0[rr] = fminf(mn0[rr], mn3); } else { mx1[rr] = fmaxf(mx1[rr], mx3); mn1[rr] = fminf(mn1[rr], mn3); }
    }
#pragma unroll
    for (int o = 1; o <= 2; o <<= 1)
#pragma unroll
        for (int rr = 0; rr < 2; rr++) {
            mx0[rr] = fmaxf(mx0[rr], __shfl_xor_sync(0xffffffffu, mx0[rr], o)); mn0[rr] = fminf(mn0[rr], __shfl_xor_sync(0xffffffffu, mn0[rr], o));
            mx1[rr] = fmaxf(mx1[rr], __shfl_xor_sync(0xffffffffu, mx1[rr], o)); mn1[rr] = fminf(mn1[rr], __shfl_xor_sync(0xffffffffu, mn1[rr], o));
        }
#pragma unroll
    for (int rr = 0; rr < 2; rr++) {
        const float a0 = -mx0[rr] * L2E, b0 = mn0[rr] * L2E, a1 = -mx1[rr] * L2E, b1 = mn1[rr] * L2E;
        const float am = lo ? a0 : a1, bm = lo ? b0 : b1;
        float ep[14], en[14];
#pragma unroll
        for (int i = 0; i < 14; i++) {
            const float x = p[4 * (i >> 1) + 2 * rr + (i & 1)];
            ep[i] = ex2(fmaf(x, L2E, i < 6 ? a0 : (i < 8 ? am : a1)));
            en[i] = ex2(fmaf(x, -L2E, i < 6 ? b0 : (i < 8 ? bm : b1)));
        }
        if (NORM) {
            float sp0 = ep[0] + ep[1] + ep[2] + ep[3] + ep[4] + ep[5], sn0 = en[0] + en[1] + en[2] + en[3] + en[4] + en[5];
            float sp1 = ep[8] + ep[9] + ep[10] + ep[11] + ep[12] + ep[13], sn1 = en[8] + en[9] + en[10] + en[11] + en[12] + en[13];
            const float sp3 = ep[6] + ep[7], sn3 = en[6] + en[7];
            if (lo) { sp0 += sp3; sn0 += sn3; } else { sp1 += sp3; sn1 += sn3; }
#pragma unroll
            for (int o = 1; o <= 2; o <<= 1) {
                sp0 += __shfl_xor_sync(0xffffffffu, sp0, o); sn0 += __shfl_xor_sync(0xffffffffu, sn0, o);
                sp1 += __shfl_xor_sync(0xffffffffu, sp1, o); sn1 += __shfl_xor_sync(0xffffffffu, sn1, o);
            }
            sp0 = rcp(sp0); sn0 = rcp(sn0); sp1 = rcp(sp1); sn1 = rcp(sn1);
            const float spm = lo ? sp0 : sp1, snm = lo ? sn0 : sn1;
#pragma unroll
            for (int i = 0; i < 14; i++) { ep[i] *= i < 6 ? sp0 : (i < 8 ? spm : sp1); en[i] *= i < 6 ? sn0 : (i < 8 ? snm : sn1); }
        }
#pragma unroll
        for (int t = 0; t < 7; t++) { f[rr][t] = pack_bf16(ep[2 * t], ep[2 * t + 1]); g[rr][t] = pack_bf16(en[2 * t], en[2 * t + 1]); }
    }
}
__device__ __forceinline__ void feature_store(uint32_t (&f)[2][7], uint32_t (&g)[2][7], uint32_t base, int r, int c) {
    const uint32_t sw = r & 7;
#pragma unroll
    for (int t = 0; t < 7; t++) {
        const bool h1 = t > 3 || (t == 3 && c >= 2);
        const int fi = 8 * t + 2 * c - (h1 ? 28 : 0);
        const uint32_t a = base + (h1 ? 16384 : 0) + r * 128 + ((((uint32_t)fi >> 3) ^ sw) << 4) + (fi & 7) * 2;
        sts32(a, f[0][t]); sts32(a ^ 64, g[0][t]); sts32(a + 1024, f[1][t]); sts32((a ^ 64) + 1024, g[1][t]);
    }
    const uint32_t z = base + (c & 1) * 16384 + (r + (c >> 1) * 8) * 128 + ((3u ^ sw) << 4) + 8;
    sts64(z, 0u, 0u); sts64(z ^ 64, 0u, 0u);
}

__device__ __forceinline__ void phi_project(float (&acc)[60], float (&p)[28], uint32_t sb) {
    uint32_t a[4][4];
#pragma unroll
    for (int kk = 0; kk < 4; kk++) {
        a[kk][0] = pack_bf16(acc[8 * kk], acc[8 * kk + 1]);
        a[kk][1] = pack_bf16(acc[8 * kk + 2], acc[8 * kk + 3]);
        a[kk][2] = kk < 3 ? pack_bf16(acc[8 * kk + 4], acc[8 * kk + 5]) : 0u;
        a[kk][3] = kk < 3 ? pack_bf16(acc[8 * kk + 6], acc[8 * kk + 7]) : 0u;
    }
#pragma unroll
    for (int i = 0; i < 28; i++) p[i] = 0.f;
    fence_regs(p); fence_regs(a);
    const uint64_t db = make_desc(sb + SM_WPHI, 8192, 1024, 1);
    WG_FENCE();
#pragma unroll
    for (int kk = 0; kk < 4; kk++) wg_rs_n56_tb1(p, a[kk], db + kk * 128, kk);
    WG_COMMIT();
    WG_WAIT(0);
    fence_regs(p);
}

__global__ void __launch_bounds__(640, 1)
fused_kernel(const __grid_constant__ CUtensorMap tmX, const __grid_constant__ CUtensorMap tmWqkv, const __grid_constant__ CUtensorMap tmWq,
             const __grid_constant__ CUtensorMap tmWoA, const __grid_constant__ CUtensorMap tmWoB, const __grid_constant__ CUtensorMap tmO,
             const __grid_constant__ CUtensorMap tmOs, const __grid_constant__ CUtensorMap tmOut,
             const __grid_constant__ CUtensorMap tmKVs,
             const __nv_bfloat16* __restrict__ w_phi, const __nv_bfloat16* __restrict__ wk, const __nv_bfloat16* __restrict__ wv,
             const __nv_bfloat16* __restrict__ gate_w, const uint8_t* __restrict__ wo_a, const uint8_t* __restrict__ wo_b) {
    extern __shared__ uint8_t smem_raw[];
    const uint32_t sb = ((uint32_t)__cvta_generic_to_shared(smem_raw) + 1023) & ~1023u;
    const int tid = threadIdx.x, lane = tid & 31;
    const int warp = __shfl_sync(0xffffffffu, tid >> 5, 0);
    const int rank = blockIdx.x & 1, hp = (blockIdx.x >> 1) & 7, tb = (blockIdx.x >> 4) * 2 + rank, cta = tb * 8 + hp;
    const int otok = tb * 128 + (hp & 1) * 64, ocol = (hp >> 1) * 128;
    auto tail_w_addr = [&](int i) -> uint32_t {
        return i == 0 || i == 9 ? SM_TW : (((i < 9 ? i - 1 : i - 10) + 3) & 7) * 16384;
    };

    if (warp >= 16) {
        const int sw = warp - 16;
        auto x_load = [&](int kb) {
            mbar_expect_tx(sb + B_XF + 8 * kb, 16384);
            tma2d(sb + SM_X + kb * 16384, &tmX, kb * 64, tb * 128, sb + B_XF + 8 * kb);
        };
        auto w_load = [&](int i) {
            const uint32_t st = sb + SM_W + (i % 5) * 16384, bar = sb + B_P1F + 8 * i;
            mbar_expect_tx(bar, 2 * 7168);
            if (i < 7) tma2d_mc(st + rank * 8192, rank ? &tmWq : &tmWqkv, hp * 56, i * 64, bar);
            else tma2d_mc(st + rank * 8192, &tmWqkv, 448 + rank * 448 + hp * 56, (i - 7) * 64, bar);
        };
        if (sw == 0) {
            if (lane == 0) {
#pragma unroll
                for (int i = 0; i < 14; i++) mbar_init(sb + B_P1F + 8 * i, 1);
#pragma unroll
                for (int i = 0; i < 7; i++) mbar_init(sb + B_XF + 8 * i, 1);
                asm volatile("fence.mbarrier_init.release.cluster;" ::: "memory");
                fence_async_smem();
                x_load(0);
            }
        } else if (sw == 1) {
            if (lane == 0) {
#pragma unroll
                for (int i = 0; i < 8; i++) { mbar_init(sb + B_RF + 8 * i, 1); mbar_init(sb + B_RE + 8 * i, 16); }
                mbar_init(sb + B_KVR, 1); mbar_init(sb + B_KVS, 1); mbar_init(sb + B_MID, 16); mbar_init(sb + B_OAD, 1); mbar_init(sb + B_OAD + 8, 1); mbar_init(sb + B_QLD, 16); mbar_init(sb + B_REL, 2); mbar_init(sb + B_KVX, 1); mbar_init(sb + B_KVX + 8, 1);
#pragma unroll
                for (int i = 0; i < 7; i++) mbar_init(sb + B_TD + 8 * i, 8);
#pragma unroll
                for (int i = 0; i < 4; i++) mbar_init(sb + B_SOW + 8 * i, 4);
                asm volatile("fence.mbarrier_init.release.cluster;" ::: "memory");
            }
        } else if (sw == 2) {
            if (lane == 0) {
#pragma unroll
                for (int i = 0; i < 18; i++) mbar_init(sb + B_P1E + 8 * i, i < 9 ? 16 : 8);
#pragma unroll
                for (int i = 0; i < 15; i++) mbar_init(sb + B_TF + 8 * i, i < 7 ? 2 : 1);
#pragma unroll
                for (int i = 0; i < 8; i++) mbar_init(sb + B_TOB + 8 * i, 1);
                asm volatile("fence.mbarrier_init.release.cluster;" ::: "memory");
            }
        }
        asm volatile("barrier.cluster.arrive.relaxed.aligned;\n\tbarrier.cluster.wait.aligned;" ::: "memory");
        asm volatile("setmaxnreg.dec.sync.aligned.u32 32;");
        if (sw == 0 && lane == 0) {
            w_load(0); x_load(1); x_load(2); w_load(1); x_load(3); x_load(4); w_load(2); x_load(5); x_load(6); w_load(3); w_load(4);
        }
        const uint32_t tag = *(volatile uint32_t*)&g_epoch + 1, par = (tag - 1) & 1;
        if (sw == 3 && lane == 0) { prefetch_map(&tmKVs); prefetch_map(&tmOs); prefetch_map(&tmO); prefetch_map(&tmWoA); prefetch_map(&tmWoB); prefetch_map(&tmOut); }
        auto ring_load = [&](int blk) {
            const uint32_t bar = sb + B_RF + 8 * (blk & 7);
            mbar_expect_tx(bar, 16384);
            bulk_g2s(sb + SM_RING + ((blk + 3) & 7) * 16384, g_kv + blk * 8192, 16384, bar);
        };
        auto tail_w_load = [&](int i) {
            const uint32_t bar = sb + B_TF + 8 * i, dst = sb + tail_w_addr(i);
            mbar_expect_tx(bar, 16384);
            if (i < 7) { tma2d(dst, &tmWoA, ocol, i * 64, bar); tma2d(dst + 8192, &tmWoA, ocol + 64, i * 64, bar); }
            else { tma3d(dst, &tmWoB, ocol, 0, 4 * (i - 7), bar); tma3d(dst + 8192, &tmWoB, ocol + 64, 0, 4 * (i - 7), bar); }
        };
        if (sw == 0) {
            if (lane == 0) {
#pragma unroll
                for (int i = 5; i < 14; i++) { mbar_wait_cluster(sb + B_P1E + 8 * (i - 5)); w_load(i); }
#pragma unroll 1
                for (int s = 0; s < 8; s++) {
                    mbar_wait_svc(sb + B_RE + 8 * s, 0); ring_load(8 + s);
                }
                mbar_wait_svc(sb + B_MID, 0); tail_w_load(0);
#pragma unroll 1
                for (int s = 0; s < 7; s++) { mbar_wait_svc(sb + B_RE + 8 * s, 1); tail_w_load(1 + s); }
#pragma unroll 1
                for (int i = 0; i < 6; i++) { mbar_wait_svc(sb + B_TD + 8 * i, 0); tail_w_load(9 + i); }
                mbar_wait_svc(sb + B_REL, 0); tail_w_load(8);
            }
        } else if (sw < 3) {
            const int x = sw - 1;
            if (x == 0) {
                *(float4*)&g_kvsum[par ^ 1][blockIdx.x * 256 + lane * 8] = make_float4(0.f, 0.f, 0.f, 0.f);
                *(float4*)&g_kvsum[par ^ 1][blockIdx.x * 256 + lane * 8 + 4] = make_float4(0.f, 0.f, 0.f, 0.f);
                mbar_wait_svc(sb + B_SKV, 0);
                if (lane == 0) {
#pragma unroll
                    for (int p = 0; p < 4; p++)
                        asm volatile("cp.async.bulk.tensor.4d.global.shared::cta.bulk_group [%0, {%2, %3, %4, %5}], [%1];" ::"l"(&tmKVs), "r"(sb + SM_SL + p * 512),
                                     "r"(8 * ((hp & 3) ^ p)), "r"(0), "r"(p), "r"(tb * 32 + (hp >> 2) * 16) : "memory");
                    asm volatile("cp.async.bulk.commit_group;" ::: "memory");
                    if (hp == 7) asm volatile("cp.async.bulk.global.shared::cta.bulk_group [%0], [%1], 512;\n\tcp.async.bulk.commit_group;" ::"l"(&g_gate[tb * 128]), "r"(sb + SM_SL + 2048) : "memory");
                }
                const uint32_t kn = __reduce_max_sync(0xffffffffu, lds32(sb + SM_WMAX + (lane & 7) * 8));
                const uint32_t vm = __reduce_max_sync(0xffffffffu, lds32(sb + SM_WMAX + (lane & 7) * 8 + 4));
                if (lane == 0) {
                    const uint64_t w = (uint64_t)tag | ((uint64_t)(((kn + 0xFFFFu) & 0xFFFF0000u) | ((vm + 0xFFFFu) >> 16)) << 32);
                    asm volatile("cp.async.bulk.wait_group 0;\n\tfence.proxy.async.global;\n\tst.release.gpu.global.b64 [%0], %1;" ::"l"(&g_f_kv[cta]), "l"(w) : "memory");
                }
            } else if (lane == 0) {
                mbar_wait_svc(sb + B_SKVA, 0);
                asm volatile("cp.reduce.async.bulk.global.shared::cta.bulk_group.add.f32 [%0], [%1], 16384;\n\tcp.async.bulk.commit_group;\n\t"
                             "cp.async.bulk.wait_group 0;\n\tfence.proxy.async.global;" ::"l"(&g_kvsum[par][2 * hp * 2048]), "r"(sb + SM_KVS) : "memory");
                flag_set(&g_f_kva[hp * 32 + tb], tag);
            }
            {
                __syncwarp();
                mbar_wait_svc(sb + B_KVS, 0);
#pragma unroll 1
                for (int w = 0; w < 4; w++) {
#pragma unroll
                    for (int i = 0; i < 8; i++) {
                        float2 a;
                        asm volatile("ld.shared.v2.f32 {%0,%1}, [%2];" : "=f"(a.x), "=f"(a.y) : "r"(sb + SM_KVS + x * 8192 + i * 1024 + (w * 32 + lane) * 8) : "memory");
                        const int fi = w * 16 + (lane >> 2) + 8 * (i & 1);
                        if (i >= 6 && (lane & 3) == 2) a.y = 1.f;
                        sts32(sb + SM_KVX + x * 4096 + fi * 64 + (((uint32_t)(i >> 1) ^ ((fi >> 1) & 3)) << 4) + (lane & 3) * 4, pack_bf16(a.x, a.y));
                    }
                }
                fence_async_smem();
                __syncwarp();
                if (lane == 0) mbar_arrive(sb + B_KVX + 8 * x);
            }
            if (lane == 0) {
                mbar_wait_svc(sb + B_SOA + 8 * x, 0);
                tma2d_store(&tmOs, sb + SM_OST + x * 8192, hp * 56, tb * 128 + x * 64);
                asm volatile("cp.async.bulk.wait_group 0;\n\tfence.proxy.async.global;" ::: "memory");
                flag_set(&g_f_oa[(tb * 2 + x) * 8 + hp], tag);
                mbar_arrive(sb + B_OAD + 8 * x);
#pragma unroll 1
                for (int hh = 1; hh >= 0; hh--) {
                    mbar_wait_svc(sb + B_SOW + 8 * (2 * x + hh), 0);
                    asm volatile("cp.async.bulk.global.shared::cta.bulk_group [%0], [%1], 4096;\n\tcp.async.bulk.commit_group;\n\tcp.async.bulk.wait_group 0;\n\tfence.proxy.async.global;"
                                 ::"l"(g_ob + ((tb * 2 + x) * 16 + hh * 8 + hp) * 4096), "r"(sb + SM_OST + (2 * x + hh) * 4096) : "memory");
                    flag_set(&g_f_ob[(tb * 2 + x) * 16 + hh * 8 + hp], tag);
                }
                mbar_arrive(sb + B_REL);
            }
        } else {
            float kn4[4], vm = 0.f;
            mbar_wait_svc(sb + B_SKV, 0);
            uint32_t pend = 15;
            for (uint32_t it = 0; it < (1u << 18); it++) {
                uint64_t a[4];
#pragma unroll
                for (int i = 0; i < 4; i++) {
                    a[i] = 0;
                    if (pend & (1u << i)) asm volatile("ld.relaxed.gpu.global.b64 %0, [%1];" : "=l"(a[i]) : "l"(&g_f_kv[i * 32 + lane]) : "memory");
                }
#pragma unroll
                for (int i = 0; i < 4; i++)
                    if ((pend & (1u << i)) && (uint32_t)a[i] == tag) {
                        pend &= ~(1u << i);
                        kn4[i] = bf_hi((uint32_t)(a[i] >> 32)); vm = fmaxf(vm, bf_lo((uint32_t)(a[i] >> 32)));
                    }
                if (__all_sync(0xffffffffu, pend == 0)) break;
            }
            asm volatile("fence.acquire.gpu;\n\tfence.proxy.async.global;" ::: "memory");
            float kn = 0.f;
#pragma unroll
            for (int i = 0; i < 4; i++) {
                float v = kn4[i];
                v += __shfl_xor_sync(0xffffffffu, v, 1); v += __shfl_xor_sync(0xffffffffu, v, 2); v += __shfl_xor_sync(0xffffffffu, v, 4);
                kn = (v <= 3.0e38f) ? fmaxf(kn, v) : 3.0e38f;
            }
            const uint32_t knu = __reduce_max_sync(0xffffffffu, __float_as_uint(kn)), vmu = __reduce_max_sync(0xffffffffu, __float_as_uint(vm));
            if (lane == 0) {
                sts64(sb + SM_KMAX, knu, vmu); mbar_arrive(sb + B_KVR);
                mbar_wait_svc(sb + B_P1E + 8 * 9, 0);
#pragma unroll
                for (int s = 0; s < 5; s++) ring_load(s);
                mbar_wait_svc(sb + B_SKVA, 0);
#pragma unroll
                for (int s = 5; s < 8; s++) ring_load(s);
            }
            __syncwarp();
            if (lane == 0) {
                asm volatile("cp.async.bulk.prefetch.L2.global [%0], 3136;" ::"l"(wo_a + cta * 3136) : "memory");
                asm volatile("cp.async.bulk.prefetch.L2.global [%0], 3136;" ::"l"(wo_b + cta * 3136) : "memory");
            }
            flags_wait(&g_f_kva[hp * 32], 16, tag, lane);
            if (lane == 0) {
                mbar_expect_tx(sb + B_KVS, 16384 + 512);
                bulk_g2s(sb + SM_KVS, &g_kvsum[par][2 * hp * 2048], 16384, sb + B_KVS);
                bulk_g2s(sb + SM_GATE, &g_gate[tb * 128], 512, sb + B_KVS);
            }
            mbar_wait_svc(sb + B_MID, 0);
            flags_wait(&g_f_oa[(tb * 2 + (hp & 1)) * 8], 8, tag, lane);
            if (lane == 0) {
#pragma unroll
                for (int i = 0; i < 7; i++) { mbar_expect_tx(sb + B_TF + 8 * i, 8192); tma2d(sb + SM_TO + i * 8192, &tmO, i * 64, otok, sb + B_TF + 8 * i); }
            }
            if (lane == 0) {
#pragma unroll
                for (int i = 0; i < 8; i++) mbar_expect_tx(sb + B_TOB + 8 * i, 8192);
            }
            const int ob = (tb * 2 + (hp & 1)) * 16;
            mbar_wait_svc(sb + B_TD + 8 * 3, 0);
            {
                uint32_t have = 0, todo = 15;
                for (uint32_t it = 0; it < (1u << 18) && todo; it++) {
                    have |= __ballot_sync(0xffffffffu, lane < 8 && !((have >> lane) & 1) && ld_relaxed(&g_f_ob[ob + 8 + lane]) == tag);
                    const uint32_t pr = have & (have >> 1), rdy = ((pr & 1) | ((pr >> 1) & 2) | ((pr >> 2) & 4) | ((pr >> 3) & 8)) & todo;
                    if (rdy) {
                        todo &= ~rdy;
                        if (mbar_try(sb + B_SOW, 0) || mbar_try(sb + B_SOW + 16, 0)) mbar_wait_svc(sb + B_REL, 0);
                        asm volatile("fence.acquire.gpu;\n\tfence.proxy.async.global;" ::: "memory");
                        __syncwarp();
                        if (lane == 0)
                            for (uint32_t m = rdy; m; m &= m - 1) { const int i = __ffs(m) - 1; bulk_g2s(sb + SM_TO + i * 8192, g_ob + (ob + 8 + 2 * i) * 4096, 8192, sb + B_TOB + 8 * i); }
                    }
                }
            }
            mbar_wait_svc(sb + B_TD + 8 * 6, 0);
            mbar_wait_svc(sb + B_SOW, 0); mbar_wait_svc(sb + B_SOW + 16, 0);
            flags_wait(&g_f_ob[ob], 8, tag, lane);
            if (lane == 0) {
#pragma unroll
                for (int i = 0; i < 4; i++) bulk_g2s(i < 3 ? sb + SM_TO + (4 + i) * 8192 : sb + SM_Q0, g_ob + (ob + 2 * i) * 4096, 8192, sb + B_TOB + 8 * (4 + i));
            }
        }
    } else {
        const int wg = warp >> 2, wq = warp & 3, th = wg >> 1, sp = wg & 1;
        const int r = wq * 16 + (lane >> 2), c = lane & 3;
        uint32_t f[2][7], g[2][7];
        float o[16];
        {
            const uint64_t da0 = make_desc(sb + SM_X + th * 8192, 16, 1024, 1);
            if (sp == 0) {
                const int w1 = th * 4 + wq, t1 = w1 * 32 + lane;
                uint2 sl[2][2];
                if (w1 < 7) {
#pragma unroll
                    for (int i = 0; i < 2; i++) {
                        const int k = w1 * 64 + lane + 32 * i;
#pragma unroll
                        for (int hh = 0; hh < 2; hh++) {
                            const int col = 8 * (hp & 3) + 4 * hh;
                            uint2 v = make_uint2(0u, 0u);
                            if (col < 28) v = __ldg((const uint2*)((hp < 4 ? wk : wv) + k * 28 + col));
                            if (hh == 1 && hp == 7) v.x = __ldg((const unsigned short*)gate_w + k);
                            sl[i][hh] = v;
                        }
                    }
                }
                uint32_t wv8[8];
#pragma unroll
                for (int i = 0; i < 8; i++) {
                    const int w = t1 + 256 * i, k = w >> 5, n = (w & 31) * 2;
                    const int hk = k >= 28, hn = n >= 28;
                    wv8[i] = (k < 56 && n < 56 && hk == hn) ? __ldg((const uint32_t*)(w_phi + (2 * hp + hk) * 784 + (k - 28 * hk) * 28 + (n - 28 * hn))) : 0u;
                }
                asm volatile("barrier.cluster.arrive.relaxed.aligned;\n\tbarrier.cluster.wait.aligned;" ::: "memory");
                asm volatile("setmaxnreg.inc.sync.aligned.u32 112;");
                if (w1 < 7) {
#pragma unroll
                    for (int i = 0; i < 2; i++) sts128(sb + SM_SW + (w1 * 64 + lane + 32 * i) * 16, sl[i][0].x, sl[i][0].y, sl[i][1].x, sl[i][1].y);
                }
#pragma unroll
                for (int i = 0; i < 8; i++) {
                    const int w = t1 + 256 * i, k = w >> 5, n = (w & 31) * 2;
                    sts32(sb + SM_WPHI + k * 128 + ((((uint32_t)n >> 3) ^ (k & 7)) << 4) + (n & 7) * 2, wv8[i]);
                }
                fence_async_smem();
                __syncwarp();
                if (lane == 0) mbar_arrive(sb + B_WPR);
                mbar_wait(sb + B_WPR, 0);
                float sa[4] = {0.f, 0.f, 0.f, 0.f};
                fence_regs(sa);
                const uint64_t dsw = make_desc(sb + SM_SW, 128, 128, 0);
#pragma unroll
                for (int kb = 0; kb < 7; kb++) {
                    mbar_wait(sb + B_XF + 8 * kb, 0);
                    WG_FENCE();
#pragma unroll
                    for (int kk = 0; kk < 4; kk++) wg_ss_n8_ta0_tb1(sa, da0 + (uint64_t)(kb * 1024 + kk * 2), dsw + (uint64_t)((kb * 4 + kk) * 16), (kb | kk) != 0);
                    WG_COMMIT();
                }
                WG_WAIT(0);
                fence_regs(sa);
                const bool extra = (hp & 3) == 3 && c >= 2;
                float kn = 0.f, vm = 0.f;
#pragma unroll
                for (int rr = 0; rr < 2; rr++) {
                    const int kr = th * 64 + r + 8 * rr;
                    const bool poly = (PMASK >> (kr >> 3)) & 1;
                    const float v0 = sa[2 * rr], v1 = sa[2 * rr + 1];
                    uint32_t pk = pack_bf16(v0, v1);
                    const float f0 = bf_lo(pk), f1 = bf_hi(pk);
                    const bool dbl = poly && hp < 4;
                    float k2 = (hp < 4 && !extra) ? f0 * f0 + f1 * f1 : 0.f;
                    const float a = (hp >= 4 && !extra) ? fabsf(f0) + fabsf(f1) : 0.f;
                    vm = (a <= 3.0e38f) ? fmaxf(vm, a) : 3.0e38f;
                    const float gt = rcp(1.f + ex2(-1.4426950408889634f * v0));
                    if (hp == 7 && c == 2) sts32(sb + SM_SL + 2048 + kr * 4, __float_as_uint(gt));
                    if (dbl) pk = pack_bf16(2.f * f0, 2.f * f1);
                    if (extra) pk = c == 2 ? (dbl ? 0x44404000u : 0x00003F80u) : (dbl ? 0x0000BFFFu : 0u);
                    sts32(sb + SM_SL + ((kr >> 1) & 3) * 512 + (kr >> 3) * 32 + (kr & 1) * 16 + c * 4, pk);
                    k2 += __shfl_xor_sync(0xffffffffu, k2, 1); k2 += __shfl_xor_sync(0xffffffffu, k2, 2);
                    kn = (k2 <= 3.0e38f) ? fmaxf(kn, k2) : 3.0e38f;
                }
                fence_async_smem();
                const uint32_t knu = __reduce_max_sync(0xffffffffu, __float_as_uint(kn)), vmu = __reduce_max_sync(0xffffffffu, __float_as_uint(vm));
                if (lane == 0) { sts64(sb + SM_WMAX + (th * 4 + wq) * 8, knu, vmu); mbar_arrive(sb + B_SKV); }
            } else {
                asm volatile("barrier.cluster.arrive.relaxed.aligned;\n\tbarrier.cluster.wait.aligned;" ::: "memory");
                asm volatile("setmaxnreg.inc.sync.aligned.u32 112;");
            }
            float acc[60];
#pragma unroll
            for (int i = 0; i < 60; i++) acc[i] = 0.f;
            fence_regs(acc);
            const uint64_t db0 = make_desc(sb + SM_W, 8192, 1024, 1);
#pragma unroll
            for (int kb = 0; kb < 7; kb++) {
                if (sp == 1) mbar_wait(sb + B_XF + 8 * kb, 0);
                mbar_wait(sb + B_P1F + 8 * (kb + 7 - 7 * sp), 0);
                const uint64_t db = db0 + (uint64_t)((sp ? kb % 5 : (kb + 2) % 5) * 1024);
                WG_FENCE();
#pragma unroll
                for (int kk = 0; kk < 4; kk++) wg_ss_n120_ta0_tb1(acc, da0 + (uint64_t)(kb * 1024 + kk * 2), db + (uint64_t)(kk * 128), (kb | kk) != 0);
                WG_COMMIT();
                if (kb >= 1) {
                    WG_WAIT(1);
                    if (lane == 0 && (sp == 1 || kb <= 2)) mbar_arrive_both(sb + B_P1E + 8 * (kb - 1 + 7 - 7 * sp), rank ^ 1);
                }
            }
            WG_WAIT(0);
            fence_regs(acc);
            uint32_t vp[2][7];
            if (sp == 0) {
                if (lane == 0) mbar_arrive(sb + B_P1E + 8 * 9);
#pragma unroll
                for (int t = 0; t < 7; t++) { vp[0][t] = pack_bf16(acc[32 + 4 * t], acc[33 + 4 * t]); vp[1][t] = pack_bf16(acc[34 + 4 * t], acc[35 + 4 * t]); }
            } else {
                if (lane == 0) mbar_arrive_both(sb + B_P1E + 8 * 6, rank ^ 1);
                mbar_wait(sb + B_SKV, 0);
                const float qs = 0.18898223650461362f * 1.4426950408889634f;
#pragma unroll
                for (int t = 0; t < 7; t++) {
                    const bool h1 = t > 3 || (t == 3 && c >= 2);
                    const int d = 8 * t + 2 * c - (h1 ? 28 : 0), tl = th * 2 + (h1 ? 1 : 0);
                    const uint32_t a = d < 16 ? sb + SM_Q0 + tl * 2048 + r * 32 + ((((uint32_t)d >> 3) ^ ((r >> 2) & 1)) << 4) + (d & 7) * 2
                                              : sb + SM_QEXT + tl * 3072 + r * 48 + (d - 16) * 2;
                    sts32(a, pack_bf16(acc[32 + 4 * t] * qs, acc[33 + 4 * t] * qs));
                    sts32(a + (d < 16 ? 256 : 384), pack_bf16(acc[34 + 4 * t] * qs, acc[35 + 4 * t] * qs));
                }
                fence_async_smem();
                __syncwarp();
                if (lane == 0) mbar_arrive(sb + B_QRD);
            }
            mbar_wait(sb + B_WPR, 0);
            float p[28];
            phi_project(acc, p, sb);
            if (sp == 0) {
                feature_map<true>(p, f, g, c);
                mbar_wait(sb + B_P1E + 8 * 9, 0);
                feature_store(f, g, sb + SM_PHIK + th * 8192, r, c);
#pragma unroll
                for (int t = 0; t < 7; t++) {
                    const bool h1 = t > 3 || (t == 3 && c >= 2);
                    const int d = 8 * t + 2 * c - (h1 ? 28 : 0);
                    const uint32_t a = sb + SM_VEXT + (h1 ? 8192 : 0) + (th * 64 + r) * 64 + ((((uint32_t)d >> 3) ^ ((r >> 1) & 3)) << 4) + (d & 7) * 2;
                    sts32(a, vp[0][t]); sts32(a + 512, vp[1][t]);
                }
                sts64(sb + SM_VEXT + (c & 1) * 8192 + (th * 64 + r + 8 * (c >> 1)) * 64 + ((3u ^ ((r >> 1) & 3)) << 4) + 8, 0x00003F80u, 0u);
                fence_async_smem();
                bar_sync(5, 256);
#pragma unroll
                for (int i = 0; i < 16; i++) o[i] = 0.f;
                fence_regs(o);
                const uint64_t da = make_desc(sb + SM_PHIK + th * 16384, 8192, 1024, 1), db = make_desc(sb + SM_VEXT + th * 8192, 512, 512, 2);
                WG_FENCE();
#pragma unroll
                for (int kk = 0; kk < 8; kk++) wg_ss_n32_ta1_tb1(o, da + kk * 128, db + kk * 64, kk);
                WG_COMMIT();
                mbar_wait(sb + B_QRD, 0);
            } else {
                feature_map<false>(p, f, g, c);
                mbar_wait(sb + B_P1E + 8 * 9, 0);
                feature_store(f, g, sb + SM_PHIQ + th * 8192, r, c);
                fence_async_smem();
#pragma unroll
                for (int i = 0; i < 16; i++) o[i] = 0.f;
                fence_regs(o);
            }
        }

        const int hh = wg & 1;
        uint32_t q1[4];
        bool fast;
        {
            const uint32_t qa = sb + SM_QEXT + wg * 3072 + r * 48 + c * 4, qz = sb + SM_Q0 + wg * 2048 + r * 32 + c * 4;
            uint32_t q0[4];
            q0[0] = lds32(qz); q0[1] = lds32(qz + 256); q0[2] = lds32(qz + 16); q0[3] = lds32(qz + 16 + 256);
            q1[0] = lds32(qa); q1[1] = lds32(qa + 384); q1[2] = lds32(qa + 16); q1[3] = lds32(qa + 16 + 384);
            if (c >= 2) { q1[2] = 0u; q1[3] = 0u; }
            float n0 = 0.f, n1 = 0.f;
#pragma unroll
            for (int i = 0; i < 4; i += 2) {
                n0 += bf_lo(q0[i]) * bf_lo(q0[i]) + bf_hi(q0[i]) * bf_hi(q0[i]) + bf_lo(q1[i]) * bf_lo(q1[i]) + bf_hi(q1[i]) * bf_hi(q1[i]);
                n1 += bf_lo(q0[i + 1]) * bf_lo(q0[i + 1]) + bf_hi(q0[i + 1]) * bf_hi(q0[i + 1]) + bf_lo(q1[i + 1]) * bf_lo(q1[i + 1]) + bf_hi(q1[i + 1]) * bf_hi(q1[i + 1]);
            }
            n0 += __shfl_xor_sync(0xffffffffu, n0, 1); n0 += __shfl_xor_sync(0xffffffffu, n0, 2);
            n1 += __shfl_xor_sync(0xffffffffu, n1, 1); n1 += __shfl_xor_sync(0xffffffffu, n1, 2);
            if (lane == 0) mbar_arrive(sb + B_QLD);
            mbar_wait(sb + B_KVR, 0);
            const float km = __uint_as_float(lds32(sb + SM_KMAX)), vmax = __uint_as_float(lds32(sb + SM_KMAX + 4));
            float b0, b1;
            asm("sqrt.approx.f32 %0, %1;" : "=f"(b0) : "f"(n0 * km * 1.002f)); asm("sqrt.approx.f32 %0, %1;" : "=f"(b1) : "f"(n1 * km * 1.002f));
            const bool ok = b0 <= 90.f && b1 <= 90.f && vmax <= 1.0e12f;
            uint32_t okall;
            asm volatile("{.reg .pred p, q; setp.ne.b32 p, %1, 0; bar.red.and.pred q, %2, 128, p; selp.b32 %0, 1, 0, q;}" : "=r"(okall) : "r"((uint32_t)ok), "r"(1 + wg) : "memory");
            fast = okall != 0;
            if (fast) {
                if (c == 2) { q1[2] = pack_bf16(64.f - b0, 1.f); q1[3] = pack_bf16(64.f - b1, 1.f); }
                if (c == 3) { q1[2] = 0x00003F80u; q1[3] = 0x00003F80u; }
            }
        }
        WG_WAIT(0);
        fence_regs(o);
        if (sp == 0) {
#pragma unroll
            for (int i = 0; i < 8; i++) sts64(sb + SM_KVS + th * 8192 + i * 1024 + (tid & 127) * 8, __float_as_uint(o[2 * i]), __float_as_uint(o[2 * i + 1]));
            fence_async_smem();
            __syncwarp();
            if (lane == 0) mbar_arrive(sb + B_SKVA);
        }
        {
            uint32_t one = 0x3F803F80u;
            asm volatile("" : "+r"(one));
            float s[64];
            uint32_t p[8][4];
            float m0 = -1.0e30f, m1 = -1.0e30f;
#pragma unroll
            for (int i = 0; i < 16; i++) o[i] = 0.f;
#pragma unroll
            for (int i = 0; i < 64; i++) s[i] = 0.f;
            fence_regs(o); fence_regs(s);
            const uint32_t klo = __shfl_sync(0xffffffffu, (uint32_t)make_desc(sb + SM_RING, 16, 512, 2), 0);
            const uint32_t qlo = __shfl_sync(0xffffffffu, (uint32_t)make_desc(sb + SM_Q0 + wg * 2048, 16, 256, 3), 0);
            const uint32_t rbar = __shfl_sync(0xffffffffu, sb + B_RF, 0);
            const int jmid = __shfl_sync(0xffffffffu, MID + ((wg + 1) >> 1), 0);
            auto d64 = [](uint32_t lo, uint32_t hi) { return ((uint64_t)hi << 32) | lo; };
            const uint64_t dq = d64(qlo, 0xC0000010u);
            mbar_wait(sb + B_RF, 0);
            WG_FENCE();
            wg_ss_n128_ta0_tb0(s, dq, d64(klo + 3 * 1024, 0x80000020u), 0);
            wg_rs_n128_tb0(s, q1, d64(klo + 3 * 1024 + 2, 0x80000020u), 1);
            WG_COMMIT();
            uint32_t so = 3 * 1024;
#pragma unroll 1
            for (int j = 0;; j++) {
                WG_WAIT(0);
                fence_regs(s);
                const uint64_t dvv = d64(klo + so + (512 + (31 << 16)), 0x80000020u);
                if (fast) {
#pragma unroll
                    for (int t = 0; t < 16; t++) {
                        uint32_t r0, r1;
                        if ((PMASK >> t) & 1) {
                            r0 = exp2_pair_fma(s[4 * t], s[4 * t + 1], one);
                            r1 = exp2_pair_fma(s[4 * t + 2], s[4 * t + 3], one);
                        } else {
                            r0 = pack_bf16(ex2(s[4 * t]), ex2(s[4 * t + 1]));
                            r1 = pack_bf16(ex2(s[4 * t + 2]), ex2(s[4 * t + 3]));
                        }
                        p[t >> 1][(t & 1) * 2] = r0; p[t >> 1][(t & 1) * 2 + 1] = r1;
                    }
                } else {
                    float x0 = m0, x1 = m1;
#pragma unroll
                    for (int t = 0; t < 16; t++) {
                        const float sc = ((PMASK >> t) & 1) ? 0.5f : 1.f;
                        x0 = fmaxf(x0, sc * fmaxf(s[4 * t], s[4 * t + 1])); x1 = fmaxf(x1, sc * fmaxf(s[4 * t + 2], s[4 * t + 3]));
                    }
                    x0 = fmaxf(x0, __shfl_xor_sync(0xffffffffu, x0, 1)); x0 = fmaxf(x0, __shfl_xor_sync(0xffffffffu, x0, 2));
                    x1 = fmaxf(x1, __shfl_xor_sync(0xffffffffu, x1, 1)); x1 = fmaxf(x1, __shfl_xor_sync(0xffffffffu, x1, 2));
                    const float c0 = ex2(m0 - x0), c1 = ex2(m1 - x1);
                    m0 = x0; m1 = x1;
#pragma unroll
                    for (int t = 0; t < 4; t++) { o[4 * t] *= c0; o[4 * t + 1] *= c0; o[4 * t + 2] *= c1; o[4 * t + 3] *= c1; }
#pragma unroll
                    for (int t = 0; t < 16; t++) {
                        const float sc = ((PMASK >> t) & 1) ? 0.5f : 1.f;
                        p[t >> 1][(t & 1) * 2] = pack_bf16(ex2(fmaf(s[4 * t], sc, -x0)), ex2(fmaf(s[4 * t + 1], sc, -x0)));
                        p[t >> 1][(t & 1) * 2 + 1] = pack_bf16(ex2(fmaf(s[4 * t + 2], sc, -x1)), ex2(fmaf(s[4 * t + 3], sc, -x1)));
                    }
                }
                fence_regs(p); fence_regs(o);
                WG_FENCE();
#pragma unroll
                for (int kk = 0; kk < 8; kk++) wg_rs_n32_tb1(o, p[kk], dvv + kk * 64, 1);
                WG_COMMIT();
                so = (so + 1024) & 0x1FFF;
                if (j < 15) mbar_wait(rbar + 8 * ((j + 1) & 7), (j + 1) >> 3);
                WG_WAIT(0);
                fence_regs(o);
                if (lane == 0) mbar_arrive(rbar + 64 + 8 * (j & 7));
                if (j == jmid) {
                    mbar_wait(sb + B_KVS, 0);
                    mbar_wait(sb + B_QLD, 0);
                    mbar_wait(sb + B_KVX + 8 * hh, 0);
                    float nm[16], nn[16];
#pragma unroll
                    for (int i = 0; i < 16; i++) { nm[i] = 0.f; nn[i] = 0.f; }
                    fence_regs(nm); fence_regs(nn);
                    const uint64_t da = make_desc(sb + SM_PHIQ + (hh * 2 + th) * 8192, 16, 1024, 1), db = make_desc(sb + SM_KVX + hh * 4096, 512, 512, 2);
                    WG_FENCE();
                    wg_ss_n32_ta0_tb1(nm, da, db, 0); wg_ss_n32_ta0_tb1(nm, da + 2, db + 64, 1);
                    wg_ss_n32_ta0_tb1(nn, da + 4, db + 128, 0); wg_ss_n32_ta0_tb1(nn, da + 6, db + 192, 1);
                    WG_COMMIT();
                    WG_WAIT(0);
                    fence_regs(nm); fence_regs(nn);
                    if (lane == 0) mbar_arrive(sb + B_MID);
                    const float g0 = __uint_as_float(lds32(sb + SM_GATE + (th * 64 + r) * 4)), g1 = __uint_as_float(lds32(sb + SM_GATE + (th * 64 + r + 8) * 4));
                    float up0 = rcp(nm[13]), un0 = rcp(nn[13]), up1 = rcp(nm[15]), un1 = rcp(nn[15]);
                    const float s0 = g0 * rcp(nm[12] * up0 + nn[12] * un0 + 1e-6f), s1 = g1 * rcp(nm[14] * up1 + nn[14] * un1 + 1e-6f);
                    const int src = (lane & ~3) | 2;
                    up0 = __shfl_sync(0xffffffffu, up0 * s0, src); un0 = __shfl_sync(0xffffffffu, un0 * s0, src);
                    up1 = __shfl_sync(0xffffffffu, up1 * s1, src); un1 = __shfl_sync(0xffffffffu, un1 * s1, src);
                    const uint32_t dst = sb + SM_OST + th * 8192 + r * 112 + hh * 56 + c * 4;
#pragma unroll
                    for (int t4 = 0; t4 < 4; t4++)
                        if (t4 < 3 || c < 2) {
                            sts32(dst + 16 * t4, pack_bf16(nm[4 * t4] * up0 + nn[4 * t4] * un0, nm[4 * t4 + 1] * up0 + nn[4 * t4 + 1] * un0));
                            sts32(dst + 16 * t4 + 896, pack_bf16(nm[4 * t4 + 2] * up1 + nn[4 * t4 + 2] * un1, nm[4 * t4 + 3] * up1 + nn[4 * t4 + 3] * un1));
                        }
                    fence_async_smem();
                    __syncwarp();
                    if (lane == 0) mbar_arrive(sb + B_SOA + 8 * th);
                }
                if (j == 15) break;
                WG_FENCE();
                const uint64_t dkk = d64(klo + so, 0x80000020u);
                wg_ss_n128_ta0_tb0(s, dq, dkk, 0);
                wg_rs_n128_tb0(s, q1, dkk + 2, 1);
                WG_COMMIT();
            }
            {
                mbar_wait(sb + B_OAD + 8 * th, 0);
                const float g0 = __uint_as_float(lds32(sb + SM_GATE + (th * 64 + r) * 4)), g1 = __uint_as_float(lds32(sb + SM_GATE + (th * 64 + r + 8) * 4));
                const float l0 = __shfl_sync(0xffffffffu, o[12], (lane & ~3) | 2), l1 = __shfl_sync(0xffffffffu, o[14], (lane & ~3) | 2);
                const float s0 = (1.f - g0) * rcp(l0), s1 = (1.f - g1) * rcp(l1);
                const uint32_t dst = sb + SM_OST + wg * 4096 + r * 64;
#pragma unroll
                for (int t4 = 0; t4 < 4; t4++) {
                    const bool pad = t4 == 3 && c >= 2;
                    const int v = 8 * t4 + 2 * c, pos = pad ? 14 + 16 * (c - 2) : v + (v >= 14 ? 2 : 0);
                    const uint32_t a = dst + ((((uint32_t)pos >> 3) ^ ((r >> 1) & 3)) << 4) + (pos & 7) * 2;
                    sts32(a, pad ? 0u : pack_bf16(o[4 * t4] * s0, o[4 * t4 + 1] * s0));
                    sts32(a + 512, pad ? 0u : pack_bf16(o[4 * t4 + 2] * s1, o[4 * t4 + 3] * s1));
                }
                fence_async_smem();
                __syncwarp();
                if (lane == 0) mbar_arrive(sb + B_SOW + 8 * wg);
            }
        }

        if (wg & 1) {
            float acc[32];
#pragma unroll
            for (int i = 0; i < 32; i++) acc[i] = 0.f;
            fence_regs(acc);
#pragma unroll 1
            for (int i = 0; i < 7; i++) {
                mbar_wait(sb + B_TF + 8 * i, 0);
                const uint64_t da = make_desc(sb + SM_TO + i * 8192, 16, 1024, 1), db = make_desc(sb + tail_w_addr(i) + th * 8192, 8192, 1024, 1);
                WG_FENCE();
#pragma unroll
                for (int kk = 0; kk < 4; kk++) wg_ss_n64_ta0_tb1(acc, da + kk * 2, db + kk * 128, 1);
                WG_COMMIT();
                WG_WAIT(0);
                if (lane == 0) mbar_arrive(sb + B_TD + 8 * i);
            }
#pragma unroll
            for (int i = 0; i < 16; i++) {
                const int bh = i < 8 ? 1 : 0, p = i < 8 ? (i + 2) & 7 : i - 8, sl = (1 - bh) * 4 + (p >> 1);
                if (bh) mbar_wait(sb + B_TF + 8 * (7 + p), 0);
                if ((p & 1) == 0) mbar_wait(sb + B_TOB + 8 * sl, 0);
                const uint64_t da = make_desc((sl < 7 ? sb + SM_TO + sl * 8192 : sb + SM_Q0) + (p & 1) * 4096, 16, 512, 2);
                const uint64_t db = make_desc(sb + tail_w_addr(7 + p) + th * 8192 + bh * 4096, 8192, 1024, 1);
                WG_FENCE();
                wg_ss_n64_ta0_tb1(acc, da, db, 1);
                wg_ss_n64_ta0_tb1(acc, da + 2, db + 128, 1);
                WG_COMMIT();
            }
            WG_WAIT(0);
            fence_regs(acc);
            const uint32_t ost = sb + tail_w_addr(6) + th * 8192, dst = ost + r * 128 + c * 4;
#pragma unroll
            for (int t = 0; t < 8; t++) {
                const uint32_t a = dst + (((uint32_t)t ^ (r & 7)) << 4);
                sts32(a, pack_bf16(acc[4 * t], acc[4 * t + 1]));
                sts32(a + 1024, pack_bf16(acc[4 * t + 2], acc[4 * t + 3]));
            }
            fence_async_smem();
            bar_sync(1 + wg, 128);
            if ((tid & 127) == 0 && (th == 0 || hp < 6)) {
                tma2d_store(&tmOut, ost, ocol + th * 64, otok);
                asm volatile("cp.async.bulk.wait_group.read 0;" ::: "memory");
            }
            if (tid == 128) {
                const uint32_t e1 = *(volatile uint32_t*)&g_epoch + 1;
                const uint32_t d = atomicAdd(&g_done, 1u);
                if (d + 1 == e1 * 128) *(volatile uint32_t*)&g_epoch = e1;
            }
        }
    }
}

typedef CUresult (*EncodeFn)(CUtensorMap*, CUtensorMapDataType, cuuint32_t, void*, const cuuint64_t*, const cuuint64_t*, const cuuint32_t*,
                             const cuuint32_t*, CUtensorMapInterleave, CUtensorMapSwizzle, CUtensorMapL2promotion, CUtensorMapFloatOOBfill);

void make_map(EncodeFn enc, CUtensorMap* tm, const void* ptr, uint64_t cols, uint64_t rows, uint32_t bc, uint32_t br, int swz = 128) {
    cuuint64_t gd[2] = {cols, rows}, gs[1] = {cols * 2};
    cuuint32_t box[2] = {bc, br}, es[2] = {1, 1};
    enc(tm, CU_TENSOR_MAP_DATA_TYPE_BFLOAT16, 2, (void*)ptr, gd, gs, box, es, CU_TENSOR_MAP_INTERLEAVE_NONE, swz == 128 ? CU_TENSOR_MAP_SWIZZLE_128B : CU_TENSOR_MAP_SWIZZLE_NONE,
        CU_TENSOR_MAP_L2_PROMOTION_L2_256B, CU_TENSOR_MAP_FLOAT_OOB_FILL_NONE);
}

}

extern "C" void kernel_launch(void* const* d_in, const int* in_sizes, int n_in, void* d_out, int out_size) {
    (void)in_sizes; (void)n_in; (void)out_size;
    static EncodeFn enc = nullptr;
    static void *ocat = nullptr, *kvp = nullptr;
    if (!enc) {
        void* fn = nullptr;
        cudaDriverEntryPointQueryResult qr;
        cudaGetDriverEntryPoint("cuTensorMapEncodeTiled", &fn, cudaEnableDefault, &qr);
        enc = (EncodeFn)fn;
        cudaGetSymbolAddress(&ocat, g_ocat);
        cudaGetSymbolAddress(&kvp, g_kv);
        cudaFuncSetAttribute(fused_kernel, cudaFuncAttributeMaxDynamicSharedMemorySize, SM_TOTAL);
    }
    CUtensorMap tmX, tmWqkv, tmWq, tmWoA, tmWoB, tmO, tmOs, tmOut, tmKVs;
    make_map(enc, &tmX, d_in[0], 448, 2048, 64, 128);
    make_map(enc, &tmWqkv, d_in[1], 1344, 448, 56, 64);
    make_map(enc, &tmWq, d_in[5], 448, 448, 56, 64);
    make_map(enc, &tmWoA, d_in[3], 448, 448, 64, 64);
    {
        cuuint64_t gd[3] = {448, 14, 32}, gs[2] = {896, 14 * 896};
        cuuint32_t box[3] = {64, 16, 4}, es[3] = {1, 1, 1};
        enc(&tmWoB, CU_TENSOR_MAP_DATA_TYPE_BFLOAT16, 3, d_in[8], gd, gs, box, es, CU_TENSOR_MAP_INTERLEAVE_NONE, CU_TENSOR_MAP_SWIZZLE_128B,
            CU_TENSOR_MAP_L2_PROMOTION_L2_256B, CU_TENSOR_MAP_FLOAT_OOB_FILL_NONE);
    }
    make_map(enc, &tmO, ocat, 448, 2048, 64, 64);
    make_map(enc, &tmOs, ocat, 448, 2048, 56, 64, 0);
    make_map(enc, &tmOut, d_out, 448, 2048, 64, 64);
    {
        cuuint64_t gd[4] = {32, 2, 4, 512}, gs[3] = {64, 128, 512};
        cuuint32_t box[4] = {8, 2, 1, 16}, es[4] = {1, 1, 1, 1};
        enc(&tmKVs, CU_TENSOR_MAP_DATA_TYPE_BFLOAT16, 4, kvp, gd, gs, box, es, CU_TENSOR_MAP_INTERLEAVE_NONE, CU_TENSOR_MAP_SWIZZLE_NONE,
            CU_TENSOR_MAP_L2_PROMOTION_NONE, CU_TENSOR_MAP_FLOAT_OOB_FILL_NONE);
    }
    cudaLaunchConfig_t cfg = {};
    cfg.gridDim = dim3(128); cfg.blockDim = dim3(640); cfg.dynamicSmemBytes = SM_TOTAL; cfg.stream = cudaStreamPerThread;
    cudaLaunchAttribute at[1];
    at[0].id = cudaLaunchAttributeClusterDimension; at[0].val.clusterDim.x = 2; at[0].val.clusterDim.y = 1; at[0].val.clusterDim.z = 1;
    cfg.attrs = at; cfg.numAttrs = 1;
    cudaLaunchKernelEx(&cfg, fused_kernel, tmX, tmWqkv, tmWq, tmWoA, tmWoB, tmO, tmOs, tmOut, tmKVs, (const __nv_bfloat16*)d_in[2],
                       (const __nv_bfloat16*)d_in[6], (const __nv_bfloat16*)d_in[7], (const __nv_bfloat16*)d_in[9], (const uint8_t*)d_in[3], (const uint8_t*)d_in[8]);
}
```
